```python
import torch

def _softmax(x, axis=-1):
    return torch.softmax(x, dim=axis)
def _gelu(x):
    return torch.nn.functional.gelu(x, approximate="tanh")
def _silu(x):
    return torch.nn.functional.silu(x)
def _sigmoid(x):
    return torch.sigmoid(x)
def _layernorm(x, axis=-1, eps=1e-5):
    m = x.mean(dim=axis, keepdim=True)
    v = x.var(dim=axis, keepdim=True, unbiased=False)
    return (x - m) / torch.sqrt(v + eps)
def _scatter_add(tgt, idx, src, axis=0):
    return tgt.clone().index_add_(axis, idx, src)
def _segment_sum(src, seg, n):
    out = torch.zeros((n,) + src.shape[1:], dtype=src.dtype)
    return out.index_add_(0, seg, src)
def _pad(x, pw):
    flat = tuple(v for pair in reversed(pw) for v in pair)
    return torch.nn.functional.pad(x, flat)

kernel_name = 'concat_heads__ssm_conv_s5__ssm_conv_h3__prompt'

def setup_inputs():

    _w = (lambda a: (lambda t: t.to(torch.bfloat16) if t.is_floating_point() else t)(torch.as_tensor(a)))
    def _A_setup():
        B, S, D = 1, 2048, 640
        P = D
        Lambda_re = -0.5 * (lambda _x: torch.exp(torch.as_tensor(_x)))((lambda *s: torch.randn(*s, dtype=torch.bfloat16) * 0.2)(P))
        Lambda_im = (lambda *s: torch.randn(*s, dtype=torch.bfloat16) * 0.4)(P) * 1.0
        B_re = (lambda *s: torch.randn(*s, dtype=torch.bfloat16) * 0.2)(P, D) * (D ** -0.5)
        B_im = (lambda *s: torch.randn(*s, dtype=torch.bfloat16) * 0.2)(P, D) * (D ** -0.5)
        C_re = (lambda *s: torch.randn(*s, dtype=torch.bfloat16) * 0.2)(D, P) * (P ** -0.5)
        C_im = (lambda *s: torch.randn(*s, dtype=torch.bfloat16) * 0.2)(D, P) * (P ** -0.5)
        log_dt = (lambda *s: torch.randn(*s, dtype=torch.bfloat16) * 0.2)(P) * 0.3 - 2.0
        Dskip = (lambda *s: torch.randn(*s, dtype=torch.bfloat16) * 0.05)(D)
        return {
            "x": _w((lambda *s: torch.randn(*s, dtype=torch.bfloat16) * 0.05)(B, S, D)),
            "Lambda_re": _w(Lambda_re),
            "Lambda_im": _w(Lambda_im),
            "B_re": _w(B_re),
            "B_im": _w(B_im),
            "C_re": _w(C_re),
            "C_im": _w(C_im),
            "log_dt": _w(log_dt),
            "Dskip": _w(Dskip),
        }
    _A_in = _A_setup()

    def _B_setup():
        B, S, D = 1, 2048, 640
        ks = 4
        return {
            "q": _w((lambda *s: torch.randn(*s, dtype=torch.bfloat16) * 0.05)(B, S, D)),
            "k": _w((lambda *s: torch.randn(*s, dtype=torch.bfloat16) * 0.4)(B, S, D)),
            "v": _w((lambda *s: torch.randn(*s, dtype=torch.bfloat16) * 0.2)(B, S, D)),
            "shift_k": _w((lambda *s: torch.randn(*s, dtype=torch.bfloat16) * 0.4)(D, ks) * 0.5),
            "ssm_k": _w((lambda *s: torch.randn(*s, dtype=torch.bfloat16) * 0.4)(D, S) * (1.0 / S ** 0.5)),
            "ssm_D": _w((lambda *s: torch.randn(*s, dtype=torch.bfloat16) * 0.2)(D)),
        }
    _B_in = _B_setup()

    return {
        "A_x": _A_in["x"],
        "A_Lambda_re": _A_in["Lambda_re"],
        "A_Lambda_im": _A_in["Lambda_im"],
        "A_B_re": _A_in["B_re"],
        "A_B_im": _A_in["B_im"],
        "A_C_re": _A_in["C_re"],
        "A_C_im": _A_in["C_im"],
        "A_log_dt": _A_in["log_dt"],
        "A_Dskip": _A_in["Dskip"],
        "B_q": _B_in["q"],
        "B_k": _B_in["k"],
        "B_v": _B_in["v"],
        "B_shift_k": _B_in["shift_k"],
        "B_ssm_k": _B_in["ssm_k"],
        "B_ssm_D": _B_in["ssm_D"],
    }

def reference(A_x, A_Lambda_re, A_Lambda_im, A_B_re, A_B_im, A_C_re, A_C_im, A_log_dt, A_Dskip, B_q, B_k, B_v, B_shift_k, B_ssm_k, B_ssm_D):
    def _A_ref(x, Lambda_re, Lambda_im, B_re, B_im, C_re, C_im, log_dt, Dskip):
        Bsz, L, H = x.shape
        Lam = Lambda_re + 1j * Lambda_im
        Bmat = B_re + 1j * B_im
        Cmat = C_re + 1j * C_im
        dt = torch.exp(log_dt)
        Lam_bar = torch.exp(dt * Lam)
        B_bar = ((Lam_bar - 1.0) / Lam)[:, None] * Bmat
        Bu = torch.einsum("bld,pd->blp", x + 0j, B_bar)
        h = torch.zeros_like(Bu[:, 0, :])
        hs = []
        for t in range(L):
            h = Lam_bar[None, :] * h + Bu[:, t, :]
            hs.append(h)
        hseq = torch.stack(hs, 1)
        y = 2.0 * torch.einsum("blp,dp->bld", hseq, Cmat).real + x * Dskip[None, None, :]
        return y

    def _B_ref(q, k, v, shift_k, ssm_k, ssm_D):
        B, S, D = q.shape
        ks = shift_k.shape[-1]
        k_pad = _pad(k, ((0, 0), (ks - 1, 0), (0, 0)))
        k_shift = torch.zeros_like(k)
        for t in range(ks):
            k_shift = k_shift + k_pad[:, t:t + S, :] * shift_k[:, ks - 1 - t][None, None, :]
        kv = k_shift * v
        L = 2 * S
        kv_pad = _pad(kv, ((0, 0), (0, S), (0, 0)))
        kf_pad = _pad(ssm_k, ((0, 0), (0, S)))
        kv_f = (lambda x, axes=(-2,-1): torch.fft.rfft2(x.float(), dim=axes))(kv_pad[:, None, :, :], axes=(1, 2))
        kf_f = (lambda x, axes=(-2,-1): torch.fft.rfft2(x.float(), dim=axes))(kf_pad[:, None, :], axes=(1, 2))
        kf_f = (lambda x, *d: x.permute(*d))(kf_f, 1, 2, 0)
        y_f = kv_f * kf_f[None, :, :, :]
        y = (lambda x, s, axes=(-2,-1): torch.fft.irfft2(x, s=s, dim=axes).to(torch.bfloat16))(y_f, (1, L), axes=(1, 2))[:, 0, :S, :]
        y = y + kv * ssm_D[None, None, :]
        return q * y

    a = _A_ref(A_x, A_Lambda_re, A_Lambda_im, A_B_re, A_B_im, A_C_re, A_C_im, A_log_dt, A_Dskip)
    b = _B_ref(B_q, B_k, B_v, B_shift_k, B_ssm_k, B_ssm_D)
    return torch.concatenate([a, b], axis=-1)
```

```cpp
#include <cuda_runtime.h>
#include <cuda.h>
#include <cuda_bf16.h>
#include <stdint.h>

template<int TA, int TB> __device__ __forceinline__ void wgmma_n16(float* d, uint64_t da, uint64_t db, int sd) {
  asm volatile("{\n.reg .pred p;\nsetp.ne.b32 p, %10, 0;\n"
    "wgmma.mma_async.sync.aligned.m64n16k16.f32.bf16.bf16 {%0, %1, %2, %3, %4, %5, %6, %7}, %8, %9, p, 1, 1, %11, %12;\n}\n"
    : "+f"(d[0]), "+f"(d[1]), "+f"(d[2]), "+f"(d[3]), "+f"(d[4]), "+f"(d[5]), "+f"(d[6]), "+f"(d[7])
    : "l"(da), "l"(db), "r"(sd), "n"(TA), "n"(TB));
}
template<int TA, int TB> __device__ __forceinline__ void wgmma_n32(float* d, uint64_t da, uint64_t db, int sd) {
  asm volatile("{\n.reg .pred p;\nsetp.ne.b32 p, %18, 0;\n"
    "wgmma.mma_async.sync.aligned.m64n32k16.f32.bf16.bf16 {%0, %1, %2, %3, %4, %5, %6, %7, %8, %9, %10, %11, %12, %13, %14, %15}, %16, %17, p, 1, 1, %19, %20;\n}\n"
    : "+f"(d[0]), "+f"(d[1]), "+f"(d[2]), "+f"(d[3]), "+f"(d[4]), "+f"(d[5]), "+f"(d[6]), "+f"(d[7]), "+f"(d[8]), "+f"(d[9]), "+f"(d[10]), "+f"(d[11]), "+f"(d[12]), "+f"(d[13]), "+f"(d[14]), "+f"(d[15])
    : "l"(da), "l"(db), "r"(sd), "n"(TA), "n"(TB));
}
template<int TA, int TB> __device__ __forceinline__ void wgmma_n48(float* d, uint64_t da, uint64_t db, int sd) {
  asm volatile("{\n.reg .pred p;\nsetp.ne.b32 p, %26, 0;\n"
    "wgmma.mma_async.sync.aligned.m64n48k16.f32.bf16.bf16 {%0, %1, %2, %3, %4, %5, %6, %7, %8, %9, %10, %11, %12, %13, %14, %15, %16, %17, %18, %19, %20, %21, %22, %23}, %24, %25, p, 1, 1, %27, %28;\n}\n"
    : "+f"(d[0]), "+f"(d[1]), "+f"(d[2]), "+f"(d[3]), "+f"(d[4]), "+f"(d[5]), "+f"(d[6]), "+f"(d[7]), "+f"(d[8]), "+f"(d[9]), "+f"(d[10]), "+f"(d[11]), "+f"(d[12]), "+f"(d[13]), "+f"(d[14]), "+f"(d[15]), "+f"(d[16]), "+f"(d[17]), "+f"(d[18]), "+f"(d[19]), "+f"(d[20]), "+f"(d[21]), "+f"(d[22]), "+f"(d[23])
    : "l"(da), "l"(db), "r"(sd), "n"(TA), "n"(TB));
}
template<int TA, int TB> __device__ __forceinline__ void wgmma_n64(float* d, uint64_t da, uint64_t db, int sd) {
  asm volatile("{\n.reg .pred p;\nsetp.ne.b32 p, %34, 0;\n"
    "wgmma.mma_async.sync.aligned.m64n64k16.f32.bf16.bf16 {%0, %1, %2, %3, %4, %5, %6, %7, %8, %9, %10, %11, %12, %13, %14, %15, %16, %17, %18, %19, %20, %21, %22, %23, %24, %25, %26, %27, %28, %29, %30, %31}, %32, %33, p, 1, 1, %35, %36;\n}\n"
    : "+f"(d[0]), "+f"(d[1]), "+f"(d[2]), "+f"(d[3]), "+f"(d[4]), "+f"(d[5]), "+f"(d[6]), "+f"(d[7]), "+f"(d[8]), "+f"(d[9]), "+f"(d[10]), "+f"(d[11]), "+f"(d[12]), "+f"(d[13]), "+f"(d[14]), "+f"(d[15]), "+f"(d[16]), "+f"(d[17]), "+f"(d[18]), "+f"(d[19]), "+f"(d[20]), "+f"(d[21]), "+f"(d[22]), "+f"(d[23]), "+f"(d[24]), "+f"(d[25]), "+f"(d[26]), "+f"(d[27]), "+f"(d[28]), "+f"(d[29]), "+f"(d[30]), "+f"(d[31])
    : "l"(da), "l"(db), "r"(sd), "n"(TA), "n"(TB));
}
template<int TA, int TB> __device__ __forceinline__ void wgmma_n80(float* d, uint64_t da, uint64_t db, int sd) {
  asm volatile("{\n.reg .pred p;\nsetp.ne.b32 p, %42, 0;\n"
    "wgmma.mma_async.sync.aligned.m64n80k16.f32.bf16.bf16 {%0, %1, %2, %3, %4, %5, %6, %7, %8, %9, %10, %11, %12, %13, %14, %15, %16, %17, %18, %19, %20, %21, %22, %23, %24, %25, %26, %27, %28, %29, %30, %31, %32, %33, %34, %35, %36, %37, %38, %39}, %40, %41, p, 1, 1, %43, %44;\n}\n"
    : "+f"(d[0]), "+f"(d[1]), "+f"(d[2]), "+f"(d[3]), "+f"(d[4]), "+f"(d[5]), "+f"(d[6]), "+f"(d[7]), "+f"(d[8]), "+f"(d[9]), "+f"(d[10]), "+f"(d[11]), "+f"(d[12]), "+f"(d[13]), "+f"(d[14]), "+f"(d[15]), "+f"(d[16]), "+f"(d[17]), "+f"(d[18]), "+f"(d[19]), "+f"(d[20]), "+f"(d[21]), "+f"(d[22]), "+f"(d[23]), "+f"(d[24]), "+f"(d[25]), "+f"(d[26]), "+f"(d[27]), "+f"(d[28]), "+f"(d[29]), "+f"(d[30]), "+f"(d[31]), "+f"(d[32]), "+f"(d[33]), "+f"(d[34]), "+f"(d[35]), "+f"(d[36]), "+f"(d[37]), "+f"(d[38]), "+f"(d[39])
    : "l"(da), "l"(db), "r"(sd), "n"(TA), "n"(TB));
}
template<int TA, int TB> __device__ __forceinline__ void wgmma_n96(float* d, uint64_t da, uint64_t db, int sd) {
  asm volatile("{\n.reg .pred p;\nsetp.ne.b32 p, %50, 0;\n"
    "wgmma.mma_async.sync.aligned.m64n96k16.f32.bf16.bf16 {%0, %1, %2, %3, %4, %5, %6, %7, %8, %9, %10, %11, %12, %13, %14, %15, %16, %17, %18, %19, %20, %21, %22, %23, %24, %25, %26, %27, %28, %29, %30, %31, %32, %33, %34, %35, %36, %37, %38, %39, %40, %41, %42, %43, %44, %45, %46, %47}, %48, %49, p, 1, 1, %51, %52;\n}\n"
    : "+f"(d[0]), "+f"(d[1]), "+f"(d[2]), "+f"(d[3]), "+f"(d[4]), "+f"(d[5]), "+f"(d[6]), "+f"(d[7]), "+f"(d[8]), "+f"(d[9]), "+f"(d[10]), "+f"(d[11]), "+f"(d[12]), "+f"(d[13]), "+f"(d[14]), "+f"(d[15]), "+f"(d[16]), "+f"(d[17]), "+f"(d[18]), "+f"(d[19]), "+f"(d[20]), "+f"(d[21]), "+f"(d[22]), "+f"(d[23]), "+f"(d[24]), "+f"(d[25]), "+f"(d[26]), "+f"(d[27]), "+f"(d[28]), "+f"(d[29]), "+f"(d[30]), "+f"(d[31]), "+f"(d[32]), "+f"(d[33]), "+f"(d[34]), "+f"(d[35]), "+f"(d[36]), "+f"(d[37]), "+f"(d[38]), "+f"(d[39]), "+f"(d[40]), "+f"(d[41]), "+f"(d[42]), "+f"(d[43]), "+f"(d[44]), "+f"(d[45]), "+f"(d[46]), "+f"(d[47])
    : "l"(da), "l"(db), "r"(sd), "n"(TA), "n"(TB));
}
template<int TA, int TB> __device__ __forceinline__ void wgmma_n112(float* d, uint64_t da, uint64_t db, int sd) {
  asm volatile("{\n.reg .pred p;\nsetp.ne.b32 p, %58, 0;\n"
    "wgmma.mma_async.sync.aligned.m64n112k16.f32.bf16.bf16 {%0, %1, %2, %3, %4, %5, %6, %7, %8, %9, %10, %11, %12, %13, %14, %15, %16, %17, %18, %19, %20, %21, %22, %23, %24, %25, %26, %27, %28, %29, %30, %31, %32, %33, %34, %35, %36, %37, %38, %39, %40, %41, %42, %43, %44, %45, %46, %47, %48, %49, %50, %51, %52, %53, %54, %55}, %56, %57, p, 1, 1, %59, %60;\n}\n"
    : "+f"(d[0]), "+f"(d[1]), "+f"(d[2]), "+f"(d[3]), "+f"(d[4]), "+f"(d[5]), "+f"(d[6]), "+f"(d[7]), "+f"(d[8]), "+f"(d[9]), "+f"(d[10]), "+f"(d[11]), "+f"(d[12]), "+f"(d[13]), "+f"(d[14]), "+f"(d[15]), "+f"(d[16]), "+f"(d[17]), "+f"(d[18]), "+f"(d[19]), "+f"(d[20]), "+f"(d[21]), "+f"(d[22]), "+f"(d[23]), "+f"(d[24]), "+f"(d[25]), "+f"(d[26]), "+f"(d[27]), "+f"(d[28]), "+f"(d[29]), "+f"(d[30]), "+f"(d[31]), "+f"(d[32]), "+f"(d[33]), "+f"(d[34]), "+f"(d[35]), "+f"(d[36]), "+f"(d[37]), "+f"(d[38]), "+f"(d[39]), "+f"(d[40]), "+f"(d[41]), "+f"(d[42]), "+f"(d[43]), "+f"(d[44]), "+f"(d[45]), "+f"(d[46]), "+f"(d[47]), "+f"(d[48]), "+f"(d[49]), "+f"(d[50]), "+f"(d[51]), "+f"(d[52]), "+f"(d[53]), "+f"(d[54]), "+f"(d[55])
    : "l"(da), "l"(db), "r"(sd), "n"(TA), "n"(TB));
}
template<int TA, int TB> __device__ __forceinline__ void wgmma_n128(float* d, uint64_t da, uint64_t db, int sd) {
  asm volatile("{\n.reg .pred p;\nsetp.ne.b32 p, %66, 0;\n"
    "wgmma.mma_async.sync.aligned.m64n128k16.f32.bf16.bf16 {%0, %1, %2, %3, %4, %5, %6, %7, %8, %9, %10, %11, %12, %13, %14, %15, %16, %17, %18, %19, %20, %21, %22, %23, %24, %25, %26, %27, %28, %29, %30, %31, %32, %33, %34, %35, %36, %37, %38, %39, %40, %41, %42, %43, %44, %45, %46, %47, %48, %49, %50, %51, %52, %53, %54, %55, %56, %57, %58, %59, %60, %61, %62, %63}, %64, %65, p, 1, 1, %67, %68;\n}\n"
    : "+f"(d[0]), "+f"(d[1]), "+f"(d[2]), "+f"(d[3]), "+f"(d[4]), "+f"(d[5]), "+f"(d[6]), "+f"(d[7]), "+f"(d[8]), "+f"(d[9]), "+f"(d[10]), "+f"(d[11]), "+f"(d[12]), "+f"(d[13]), "+f"(d[14]), "+f"(d[15]), "+f"(d[16]), "+f"(d[17]), "+f"(d[18]), "+f"(d[19]), "+f"(d[20]), "+f"(d[21]), "+f"(d[22]), "+f"(d[23]), "+f"(d[24]), "+f"(d[25]), "+f"(d[26]), "+f"(d[27]), "+f"(d[28]), "+f"(d[29]), "+f"(d[30]), "+f"(d[31]), "+f"(d[32]), "+f"(d[33]), "+f"(d[34]), "+f"(d[35]), "+f"(d[36]), "+f"(d[37]), "+f"(d[38]), "+f"(d[39]), "+f"(d[40]), "+f"(d[41]), "+f"(d[42]), "+f"(d[43]), "+f"(d[44]), "+f"(d[45]), "+f"(d[46]), "+f"(d[47]), "+f"(d[48]), "+f"(d[49]), "+f"(d[50]), "+f"(d[51]), "+f"(d[52]), "+f"(d[53]), "+f"(d[54]), "+f"(d[55]), "+f"(d[56]), "+f"(d[57]), "+f"(d[58]), "+f"(d[59]), "+f"(d[60]), "+f"(d[61]), "+f"(d[62]), "+f"(d[63])
    : "l"(da), "l"(db), "r"(sd), "n"(TA), "n"(TB));
}
template<int TA, int TB> __device__ __forceinline__ void wgmma_n144(float* d, uint64_t da, uint64_t db, int sd) {
  asm volatile("{\n.reg .pred p;\nsetp.ne.b32 p, %74, 0;\n"
    "wgmma.mma_async.sync.aligned.m64n144k16.f32.bf16.bf16 {%0, %1, %2, %3, %4, %5, %6, %7, %8, %9, %10, %11, %12, %13, %14, %15, %16, %17, %18, %19, %20, %21, %22, %23, %24, %25, %26, %27, %28, %29, %30, %31, %32, %33, %34, %35, %36, %37, %38, %39, %40, %41, %42, %43, %44, %45, %46, %47, %48, %49, %50, %51, %52, %53, %54, %55, %56, %57, %58, %59, %60, %61, %62, %63, %64, %65, %66, %67, %68, %69, %70, %71}, %72, %73, p, 1, 1, %75, %76;\n}\n"
    : "+f"(d[0]), "+f"(d[1]), "+f"(d[2]), "+f"(d[3]), "+f"(d[4]), "+f"(d[5]), "+f"(d[6]), "+f"(d[7]), "+f"(d[8]), "+f"(d[9]), "+f"(d[10]), "+f"(d[11]), "+f"(d[12]), "+f"(d[13]), "+f"(d[14]), "+f"(d[15]), "+f"(d[16]), "+f"(d[17]), "+f"(d[18]), "+f"(d[19]), "+f"(d[20]), "+f"(d[21]), "+f"(d[22]), "+f"(d[23]), "+f"(d[24]), "+f"(d[25]), "+f"(d[26]), "+f"(d[27]), "+f"(d[28]), "+f"(d[29]), "+f"(d[30]), "+f"(d[31]), "+f"(d[32]), "+f"(d[33]), "+f"(d[34]), "+f"(d[35]), "+f"(d[36]), "+f"(d[37]), "+f"(d[38]), "+f"(d[39]), "+f"(d[40]), "+f"(d[41]), "+f"(d[42]), "+f"(d[43]), "+f"(d[44]), "+f"(d[45]), "+f"(d[46]), "+f"(d[47]), "+f"(d[48]), "+f"(d[49]), "+f"(d[50]), "+f"(d[51]), "+f"(d[52]), "+f"(d[53]), "+f"(d[54]), "+f"(d[55]), "+f"(d[56]), "+f"(d[57]), "+f"(d[58]), "+f"(d[59]), "+f"(d[60]), "+f"(d[61]), "+f"(d[62]), "+f"(d[63]), "+f"(d[64]), "+f"(d[65]), "+f"(d[66]), "+f"(d[67]), "+f"(d[68]), "+f"(d[69]), "+f"(d[70]), "+f"(d[71])
    : "l"(da), "l"(db), "r"(sd), "n"(TA), "n"(TB));
}
template<int TA, int TB> __device__ __forceinline__ void wgmma_n160(float* d, uint64_t da, uint64_t db, int sd) {
  asm volatile("{\n.reg .pred p;\nsetp.ne.b32 p, %82, 0;\n"
    "wgmma.mma_async.sync.aligned.m64n160k16.f32.bf16.bf16 {%0, %1, %2, %3, %4, %5, %6, %7, %8, %9, %10, %11, %12, %13, %14, %15, %16, %17, %18, %19, %20, %21, %22, %23, %24, %25, %26, %27, %28, %29, %30, %31, %32, %33, %34, %35, %36, %37, %38, %39, %40, %41, %42, %43, %44, %45, %46, %47, %48, %49, %50, %51, %52, %53, %54, %55, %56, %57, %58, %59, %60, %61, %62, %63, %64, %65, %66, %67, %68, %69, %70, %71, %72, %73, %74, %75, %76, %77, %78, %79}, %80, %81, p, 1, 1, %83, %84;\n}\n"
    : "+f"(d[0]), "+f"(d[1]), "+f"(d[2]), "+f"(d[3]), "+f"(d[4]), "+f"(d[5]), "+f"(d[6]), "+f"(d[7]), "+f"(d[8]), "+f"(d[9]), "+f"(d[10]), "+f"(d[11]), "+f"(d[12]), "+f"(d[13]), "+f"(d[14]), "+f"(d[15]), "+f"(d[16]), "+f"(d[17]), "+f"(d[18]), "+f"(d[19]), "+f"(d[20]), "+f"(d[21]), "+f"(d[22]), "+f"(d[23]), "+f"(d[24]), "+f"(d[25]), "+f"(d[26]), "+f"(d[27]), "+f"(d[28]), "+f"(d[29]), "+f"(d[30]), "+f"(d[31]), "+f"(d[32]), "+f"(d[33]), "+f"(d[34]), "+f"(d[35]), "+f"(d[36]), "+f"(d[37]), "+f"(d[38]), "+f"(d[39]), "+f"(d[40]), "+f"(d[41]), "+f"(d[42]), "+f"(d[43]), "+f"(d[44]), "+f"(d[45]), "+f"(d[46]), "+f"(d[47]), "+f"(d[48]), "+f"(d[49]), "+f"(d[50]), "+f"(d[51]), "+f"(d[52]), "+f"(d[53]), "+f"(d[54]), "+f"(d[55]), "+f"(d[56]), "+f"(d[57]), "+f"(d[58]), "+f"(d[59]), "+f"(d[60]), "+f"(d[61]), "+f"(d[62]), "+f"(d[63]), "+f"(d[64]), "+f"(d[65]), "+f"(d[66]), "+f"(d[67]), "+f"(d[68]), "+f"(d[69]), "+f"(d[70]), "+f"(d[71]), "+f"(d[72]), "+f"(d[73]), "+f"(d[74]), "+f"(d[75]), "+f"(d[76]), "+f"(d[77]), "+f"(d[78]), "+f"(d[79])
    : "l"(da), "l"(db), "r"(sd), "n"(TA), "n"(TB));
}
template<int TA, int TB> __device__ __forceinline__ void wgmma_n176(float* d, uint64_t da, uint64_t db, int sd) {
  asm volatile("{\n.reg .pred p;\nsetp.ne.b32 p, %90, 0;\n"
    "wgmma.mma_async.sync.aligned.m64n176k16.f32.bf16.bf16 {%0, %1, %2, %3, %4, %5, %6, %7, %8, %9, %10, %11, %12, %13, %14, %15, %16, %17, %18, %19, %20, %21, %22, %23, %24, %25, %26, %27, %28, %29, %30, %31, %32, %33, %34, %35, %36, %37, %38, %39, %40, %41, %42, %43, %44, %45, %46, %47, %48, %49, %50, %51, %52, %53, %54, %55, %56, %57, %58, %59, %60, %61, %62, %63, %64, %65, %66, %67, %68, %69, %70, %71, %72, %73, %74, %75, %76, %77, %78, %79, %80, %81, %82, %83, %84, %85, %86, %87}, %88, %89, p, 1, 1, %91, %92;\n}\n"
    : "+f"(d[0]), "+f"(d[1]), "+f"(d[2]), "+f"(d[3]), "+f"(d[4]), "+f"(d[5]), "+f"(d[6]), "+f"(d[7]), "+f"(d[8]), "+f"(d[9]), "+f"(d[10]), "+f"(d[11]), "+f"(d[12]), "+f"(d[13]), "+f"(d[14]), "+f"(d[15]), "+f"(d[16]), "+f"(d[17]), "+f"(d[18]), "+f"(d[19]), "+f"(d[20]), "+f"(d[21]), "+f"(d[22]), "+f"(d[23]), "+f"(d[24]), "+f"(d[25]), "+f"(d[26]), "+f"(d[27]), "+f"(d[28]), "+f"(d[29]), "+f"(d[30]), "+f"(d[31]), "+f"(d[32]), "+f"(d[33]), "+f"(d[34]), "+f"(d[35]), "+f"(d[36]), "+f"(d[37]), "+f"(d[38]), "+f"(d[39]), "+f"(d[40]), "+f"(d[41]), "+f"(d[42]), "+f"(d[43]), "+f"(d[44]), "+f"(d[45]), "+f"(d[46]), "+f"(d[47]), "+f"(d[48]), "+f"(d[49]), "+f"(d[50]), "+f"(d[51]), "+f"(d[52]), "+f"(d[53]), "+f"(d[54]), "+f"(d[55]), "+f"(d[56]), "+f"(d[57]), "+f"(d[58]), "+f"(d[59]), "+f"(d[60]), "+f"(d[61]), "+f"(d[62]), "+f"(d[63]), "+f"(d[64]), "+f"(d[65]), "+f"(d[66]), "+f"(d[67]), "+f"(d[68]), "+f"(d[69]), "+f"(d[70]), "+f"(d[71]), "+f"(d[72]), "+f"(d[73]), "+f"(d[74]), "+f"(d[75]), "+f"(d[76]), "+f"(d[77]), "+f"(d[78]), "+f"(d[79]), "+f"(d[80]), "+f"(d[81]), "+f"(d[82]), "+f"(d[83]), "+f"(d[84]), "+f"(d[85]), "+f"(d[86]), "+f"(d[87])
    : "l"(da), "l"(db), "r"(sd), "n"(TA), "n"(TB));
}
template<int TA, int TB> __device__ __forceinline__ void wgmma_n192(float* d, uint64_t da, uint64_t db, int sd) {
  asm volatile("{\n.reg .pred p;\nsetp.ne.b32 p, %98, 0;\n"
    "wgmma.mma_async.sync.aligned.m64n192k16.f32.bf16.bf16 {%0, %1, %2, %3, %4, %5, %6, %7, %8, %9, %10, %11, %12, %13, %14, %15, %16, %17, %18, %19, %20, %21, %22, %23, %24, %25, %26, %27, %28, %29, %30, %31, %32, %33, %34, %35, %36, %37, %38, %39, %40, %41, %42, %43, %44, %45, %46, %47, %48, %49, %50, %51, %52, %53, %54, %55, %56, %57, %58, %59, %60, %61, %62, %63, %64, %65, %66, %67, %68, %69, %70, %71, %72, %73, %74, %75, %76, %77, %78, %79, %80, %81, %82, %83, %84, %85, %86, %87, %88, %89, %90, %91, %92, %93, %94, %95}, %96, %97, p, 1, 1, %99, %100;\n}\n"
    : "+f"(d[0]), "+f"(d[1]), "+f"(d[2]), "+f"(d[3]), "+f"(d[4]), "+f"(d[5]), "+f"(d[6]), "+f"(d[7]), "+f"(d[8]), "+f"(d[9]), "+f"(d[10]), "+f"(d[11]), "+f"(d[12]), "+f"(d[13]), "+f"(d[14]), "+f"(d[15]), "+f"(d[16]), "+f"(d[17]), "+f"(d[18]), "+f"(d[19]), "+f"(d[20]), "+f"(d[21]), "+f"(d[22]), "+f"(d[23]), "+f"(d[24]), "+f"(d[25]), "+f"(d[26]), "+f"(d[27]), "+f"(d[28]), "+f"(d[29]), "+f"(d[30]), "+f"(d[31]), "+f"(d[32]), "+f"(d[33]), "+f"(d[34]), "+f"(d[35]), "+f"(d[36]), "+f"(d[37]), "+f"(d[38]), "+f"(d[39]), "+f"(d[40]), "+f"(d[41]), "+f"(d[42]), "+f"(d[43]), "+f"(d[44]), "+f"(d[45]), "+f"(d[46]), "+f"(d[47]), "+f"(d[48]), "+f"(d[49]), "+f"(d[50]), "+f"(d[51]), "+f"(d[52]), "+f"(d[53]), "+f"(d[54]), "+f"(d[55]), "+f"(d[56]), "+f"(d[57]), "+f"(d[58]), "+f"(d[59]), "+f"(d[60]), "+f"(d[61]), "+f"(d[62]), "+f"(d[63]), "+f"(d[64]), "+f"(d[65]), "+f"(d[66]), "+f"(d[67]), "+f"(d[68]), "+f"(d[69]), "+f"(d[70]), "+f"(d[71]), "+f"(d[72]), "+f"(d[73]), "+f"(d[74]), "+f"(d[75]), "+f"(d[76]), "+f"(d[77]), "+f"(d[78]), "+f"(d[79]), "+f"(d[80]), "+f"(d[81]), "+f"(d[82]), "+f"(d[83]), "+f"(d[84]), "+f"(d[85]), "+f"(d[86]), "+f"(d[87]), "+f"(d[88]), "+f"(d[89]), "+f"(d[90]), "+f"(d[91]), "+f"(d[92]), "+f"(d[93]), "+f"(d[94]), "+f"(d[95])
    : "l"(da), "l"(db), "r"(sd), "n"(TA), "n"(TB));
}
template<int TA, int TB> __device__ __forceinline__ void wgmma_n208(float* d, uint64_t da, uint64_t db, int sd) {
  asm volatile("{\n.reg .pred p;\nsetp.ne.b32 p, %106, 0;\n"
    "wgmma.mma_async.sync.aligned.m64n208k16.f32.bf16.bf16 {%0, %1, %2, %3, %4, %5, %6, %7, %8, %9, %10, %11, %12, %13, %14, %15, %16, %17, %18, %19, %20, %21, %22, %23, %24, %25, %26, %27, %28, %29, %30, %31, %32, %33, %34, %35, %36, %37, %38, %39, %40, %41, %42, %43, %44, %45, %46, %47, %48, %49, %50, %51, %52, %53, %54, %55, %56, %57, %58, %59, %60, %61, %62, %63, %64, %65, %66, %67, %68, %69, %70, %71, %72, %73, %74, %75, %76, %77, %78, %79, %80, %81, %82, %83, %84, %85, %86, %87, %88, %89, %90, %91, %92, %93, %94, %95, %96, %97, %98, %99, %100, %101, %102, %103}, %104, %105, p, 1, 1, %107, %108;\n}\n"
    : "+f"(d[0]), "+f"(d[1]), "+f"(d[2]), "+f"(d[3]), "+f"(d[4]), "+f"(d[5]), "+f"(d[6]), "+f"(d[7]), "+f"(d[8]), "+f"(d[9]), "+f"(d[10]), "+f"(d[11]), "+f"(d[12]), "+f"(d[13]), "+f"(d[14]), "+f"(d[15]), "+f"(d[16]), "+f"(d[17]), "+f"(d[18]), "+f"(d[19]), "+f"(d[20]), "+f"(d[21]), "+f"(d[22]), "+f"(d[23]), "+f"(d[24]), "+f"(d[25]), "+f"(d[26]), "+f"(d[27]), "+f"(d[28]), "+f"(d[29]), "+f"(d[30]), "+f"(d[31]), "+f"(d[32]), "+f"(d[33]), "+f"(d[34]), "+f"(d[35]), "+f"(d[36]), "+f"(d[37]), "+f"(d[38]), "+f"(d[39]), "+f"(d[40]), "+f"(d[41]), "+f"(d[42]), "+f"(d[43]), "+f"(d[44]), "+f"(d[45]), "+f"(d[46]), "+f"(d[47]), "+f"(d[48]), "+f"(d[49]), "+f"(d[50]), "+f"(d[51]), "+f"(d[52]), "+f"(d[53]), "+f"(d[54]), "+f"(d[55]), "+f"(d[56]), "+f"(d[57]), "+f"(d[58]), "+f"(d[59]), "+f"(d[60]), "+f"(d[61]), "+f"(d[62]), "+f"(d[63]), "+f"(d[64]), "+f"(d[65]), "+f"(d[66]), "+f"(d[67]), "+f"(d[68]), "+f"(d[69]), "+f"(d[70]), "+f"(d[71]), "+f"(d[72]), "+f"(d[73]), "+f"(d[74]), "+f"(d[75]), "+f"(d[76]), "+f"(d[77]), "+f"(d[78]), "+f"(d[79]), "+f"(d[80]), "+f"(d[81]), "+f"(d[82]), "+f"(d[83]), "+f"(d[84]), "+f"(d[85]), "+f"(d[86]), "+f"(d[87]), "+f"(d[88]), "+f"(d[89]), "+f"(d[90]), "+f"(d[91]), "+f"(d[92]), "+f"(d[93]), "+f"(d[94]), "+f"(d[95]), "+f"(d[96]), "+f"(d[97]), "+f"(d[98]), "+f"(d[99]), "+f"(d[100]), "+f"(d[101]), "+f"(d[102]), "+f"(d[103])
    : "l"(da), "l"(db), "r"(sd), "n"(TA), "n"(TB));
}
template<int TA, int TB> __device__ __forceinline__ void wgmma_n224(float* d, uint64_t da, uint64_t db, int sd) {
  asm volatile("{\n.reg .pred p;\nsetp.ne.b32 p, %114, 0;\n"
    "wgmma.mma_async.sync.aligned.m64n224k16.f32.bf16.bf16 {%0, %1, %2, %3, %4, %5, %6, %7, %8, %9, %10, %11, %12, %13, %14, %15, %16, %17, %18, %19, %20, %21, %22, %23, %24, %25, %26, %27, %28, %29, %30, %31, %32, %33, %34, %35, %36, %37, %38, %39, %40, %41, %42, %43, %44, %45, %46, %47, %48, %49, %50, %51, %52, %53, %54, %55, %56, %57, %58, %59, %60, %61, %62, %63, %64, %65, %66, %67, %68, %69, %70, %71, %72, %73, %74, %75, %76, %77, %78, %79, %80, %81, %82, %83, %84, %85, %86, %87, %88, %89, %90, %91, %92, %93, %94, %95, %96, %97, %98, %99, %100, %101, %102, %103, %104, %105, %106, %107, %108, %109, %110, %111}, %112, %113, p, 1, 1, %115, %116;\n}\n"
    : "+f"(d[0]), "+f"(d[1]), "+f"(d[2]), "+f"(d[3]), "+f"(d[4]), "+f"(d[5]), "+f"(d[6]), "+f"(d[7]), "+f"(d[8]), "+f"(d[9]), "+f"(d[10]), "+f"(d[11]), "+f"(d[12]), "+f"(d[13]), "+f"(d[14]), "+f"(d[15]), "+f"(d[16]), "+f"(d[17]), "+f"(d[18]), "+f"(d[19]), "+f"(d[20]), "+f"(d[21]), "+f"(d[22]), "+f"(d[23]), "+f"(d[24]), "+f"(d[25]), "+f"(d[26]), "+f"(d[27]), "+f"(d[28]), "+f"(d[29]), "+f"(d[30]), "+f"(d[31]), "+f"(d[32]), "+f"(d[33]), "+f"(d[34]), "+f"(d[35]), "+f"(d[36]), "+f"(d[37]), "+f"(d[38]), "+f"(d[39]), "+f"(d[40]), "+f"(d[41]), "+f"(d[42]), "+f"(d[43]), "+f"(d[44]), "+f"(d[45]), "+f"(d[46]), "+f"(d[47]), "+f"(d[48]), "+f"(d[49]), "+f"(d[50]), "+f"(d[51]), "+f"(d[52]), "+f"(d[53]), "+f"(d[54]), "+f"(d[55]), "+f"(d[56]), "+f"(d[57]), "+f"(d[58]), "+f"(d[59]), "+f"(d[60]), "+f"(d[61]), "+f"(d[62]), "+f"(d[63]), "+f"(d[64]), "+f"(d[65]), "+f"(d[66]), "+f"(d[67]), "+f"(d[68]), "+f"(d[69]), "+f"(d[70]), "+f"(d[71]), "+f"(d[72]), "+f"(d[73]), "+f"(d[74]), "+f"(d[75]), "+f"(d[76]), "+f"(d[77]), "+f"(d[78]), "+f"(d[79]), "+f"(d[80]), "+f"(d[81]), "+f"(d[82]), "+f"(d[83]), "+f"(d[84]), "+f"(d[85]), "+f"(d[86]), "+f"(d[87]), "+f"(d[88]), "+f"(d[89]), "+f"(d[90]), "+f"(d[91]), "+f"(d[92]), "+f"(d[93]), "+f"(d[94]), "+f"(d[95]), "+f"(d[96]), "+f"(d[97]), "+f"(d[98]), "+f"(d[99]), "+f"(d[100]), "+f"(d[101]), "+f"(d[102]), "+f"(d[103]), "+f"(d[104]), "+f"(d[105]), "+f"(d[106]), "+f"(d[107]), "+f"(d[108]), "+f"(d[109]), "+f"(d[110]), "+f"(d[111])
    : "l"(da), "l"(db), "r"(sd), "n"(TA), "n"(TB));
}
template<int TA, int TB> __device__ __forceinline__ void wgmma_n240(float* d, uint64_t da, uint64_t db, int sd) {
  asm volatile("{\n.reg .pred p;\nsetp.ne.b32 p, %122, 0;\n"
    "wgmma.mma_async.sync.aligned.m64n240k16.f32.bf16.bf16 {%0, %1, %2, %3, %4, %5, %6, %7, %8, %9, %10, %11, %12, %13, %14, %15, %16, %17, %18, %19, %20, %21, %22, %23, %24, %25, %26, %27, %28, %29, %30, %31, %32, %33, %34, %35, %36, %37, %38, %39, %40, %41, %42, %43, %44, %45, %46, %47, %48, %49, %50, %51, %52, %53, %54, %55, %56, %57, %58, %59, %60, %61, %62, %63, %64, %65, %66, %67, %68, %69, %70, %71, %72, %73, %74, %75, %76, %77, %78, %79, %80, %81, %82, %83, %84, %85, %86, %87, %88, %89, %90, %91, %92, %93, %94, %95, %96, %97, %98, %99, %100, %101, %102, %103, %104, %105, %106, %107, %108, %109, %110, %111, %112, %113, %114, %115, %116, %117, %118, %119}, %120, %121, p, 1, 1, %123, %124;\n}\n"
    : "+f"(d[0]), "+f"(d[1]), "+f"(d[2]), "+f"(d[3]), "+f"(d[4]), "+f"(d[5]), "+f"(d[6]), "+f"(d[7]), "+f"(d[8]), "+f"(d[9]), "+f"(d[10]), "+f"(d[11]), "+f"(d[12]), "+f"(d[13]), "+f"(d[14]), "+f"(d[15]), "+f"(d[16]), "+f"(d[17]), "+f"(d[18]), "+f"(d[19]), "+f"(d[20]), "+f"(d[21]), "+f"(d[22]), "+f"(d[23]), "+f"(d[24]), "+f"(d[25]), "+f"(d[26]), "+f"(d[27]), "+f"(d[28]), "+f"(d[29]), "+f"(d[30]), "+f"(d[31]), "+f"(d[32]), "+f"(d[33]), "+f"(d[34]), "+f"(d[35]), "+f"(d[36]), "+f"(d[37]), "+f"(d[38]), "+f"(d[39]), "+f"(d[40]), "+f"(d[41]), "+f"(d[42]), "+f"(d[43]), "+f"(d[44]), "+f"(d[45]), "+f"(d[46]), "+f"(d[47]), "+f"(d[48]), "+f"(d[49]), "+f"(d[50]), "+f"(d[51]), "+f"(d[52]), "+f"(d[53]), "+f"(d[54]), "+f"(d[55]), "+f"(d[56]), "+f"(d[57]), "+f"(d[58]), "+f"(d[59]), "+f"(d[60]), "+f"(d[61]), "+f"(d[62]), "+f"(d[63]), "+f"(d[64]), "+f"(d[65]), "+f"(d[66]), "+f"(d[67]), "+f"(d[68]), "+f"(d[69]), "+f"(d[70]), "+f"(d[71]), "+f"(d[72]), "+f"(d[73]), "+f"(d[74]), "+f"(d[75]), "+f"(d[76]), "+f"(d[77]), "+f"(d[78]), "+f"(d[79]), "+f"(d[80]), "+f"(d[81]), "+f"(d[82]), "+f"(d[83]), "+f"(d[84]), "+f"(d[85]), "+f"(d[86]), "+f"(d[87]), "+f"(d[88]), "+f"(d[89]), "+f"(d[90]), "+f"(d[91]), "+f"(d[92]), "+f"(d[93]), "+f"(d[94]), "+f"(d[95]), "+f"(d[96]), "+f"(d[97]), "+f"(d[98]), "+f"(d[99]), "+f"(d[100]), "+f"(d[101]), "+f"(d[102]), "+f"(d[103]), "+f"(d[104]), "+f"(d[105]), "+f"(d[106]), "+f"(d[107]), "+f"(d[108]), "+f"(d[109]), "+f"(d[110]), "+f"(d[111]), "+f"(d[112]), "+f"(d[113]), "+f"(d[114]), "+f"(d[115]), "+f"(d[116]), "+f"(d[117]), "+f"(d[118]), "+f"(d[119])
    : "l"(da), "l"(db), "r"(sd), "n"(TA), "n"(TB));
}
template<int TA, int TB> __device__ __forceinline__ void wgmma_n256(float* d, uint64_t da, uint64_t db, int sd) {
  asm volatile("{\n.reg .pred p;\nsetp.ne.b32 p, %130, 0;\n"
    "wgmma.mma_async.sync.aligned.m64n256k16.f32.bf16.bf16 {%0, %1, %2, %3, %4, %5, %6, %7, %8, %9, %10, %11, %12, %13, %14, %15, %16, %17, %18, %19, %20, %21, %22, %23, %24, %25, %26, %27, %28, %29, %30, %31, %32, %33, %34, %35, %36, %37, %38, %39, %40, %41, %42, %43, %44, %45, %46, %47, %48, %49, %50, %51, %52, %53, %54, %55, %56, %57, %58, %59, %60, %61, %62, %63, %64, %65, %66, %67, %68, %69, %70, %71, %72, %73, %74, %75, %76, %77, %78, %79, %80, %81, %82, %83, %84, %85, %86, %87, %88, %89, %90, %91, %92, %93, %94, %95, %96, %97, %98, %99, %100, %101, %102, %103, %104, %105, %106, %107, %108, %109, %110, %111, %112, %113, %114, %115, %116, %117, %118, %119, %120, %121, %122, %123, %124, %125, %126, %127}, %128, %129, p, 1, 1, %131, %132;\n}\n"
    : "+f"(d[0]), "+f"(d[1]), "+f"(d[2]), "+f"(d[3]), "+f"(d[4]), "+f"(d[5]), "+f"(d[6]), "+f"(d[7]), "+f"(d[8]), "+f"(d[9]), "+f"(d[10]), "+f"(d[11]), "+f"(d[12]), "+f"(d[13]), "+f"(d[14]), "+f"(d[15]), "+f"(d[16]), "+f"(d[17]), "+f"(d[18]), "+f"(d[19]), "+f"(d[20]), "+f"(d[21]), "+f"(d[22]), "+f"(d[23]), "+f"(d[24]), "+f"(d[25]), "+f"(d[26]), "+f"(d[27]), "+f"(d[28]), "+f"(d[29]), "+f"(d[30]), "+f"(d[31]), "+f"(d[32]), "+f"(d[33]), "+f"(d[34]), "+f"(d[35]), "+f"(d[36]), "+f"(d[37]), "+f"(d[38]), "+f"(d[39]), "+f"(d[40]), "+f"(d[41]), "+f"(d[42]), "+f"(d[43]), "+f"(d[44]), "+f"(d[45]), "+f"(d[46]), "+f"(d[47]), "+f"(d[48]), "+f"(d[49]), "+f"(d[50]), "+f"(d[51]), "+f"(d[52]), "+f"(d[53]), "+f"(d[54]), "+f"(d[55]), "+f"(d[56]), "+f"(d[57]), "+f"(d[58]), "+f"(d[59]), "+f"(d[60]), "+f"(d[61]), "+f"(d[62]), "+f"(d[63]), "+f"(d[64]), "+f"(d[65]), "+f"(d[66]), "+f"(d[67]), "+f"(d[68]), "+f"(d[69]), "+f"(d[70]), "+f"(d[71]), "+f"(d[72]), "+f"(d[73]), "+f"(d[74]), "+f"(d[75]), "+f"(d[76]), "+f"(d[77]), "+f"(d[78]), "+f"(d[79]), "+f"(d[80]), "+f"(d[81]), "+f"(d[82]), "+f"(d[83]), "+f"(d[84]), "+f"(d[85]), "+f"(d[86]), "+f"(d[87]), "+f"(d[88]), "+f"(d[89]), "+f"(d[90]), "+f"(d[91]), "+f"(d[92]), "+f"(d[93]), "+f"(d[94]), "+f"(d[95]), "+f"(d[96]), "+f"(d[97]), "+f"(d[98]), "+f"(d[99]), "+f"(d[100]), "+f"(d[101]), "+f"(d[102]), "+f"(d[103]), "+f"(d[104]), "+f"(d[105]), "+f"(d[106]), "+f"(d[107]), "+f"(d[108]), "+f"(d[109]), "+f"(d[110]), "+f"(d[111]), "+f"(d[112]), "+f"(d[113]), "+f"(d[114]), "+f"(d[115]), "+f"(d[116]), "+f"(d[117]), "+f"(d[118]), "+f"(d[119]), "+f"(d[120]), "+f"(d[121]), "+f"(d[122]), "+f"(d[123]), "+f"(d[124]), "+f"(d[125]), "+f"(d[126]), "+f"(d[127])
    : "l"(da), "l"(db), "r"(sd), "n"(TA), "n"(TB));
}
template<int N, int TA, int TB> __device__ __forceinline__ void wgmma_ss(float* d, uint64_t da, uint64_t db, int sd) {
  if constexpr (N == 16) wgmma_n16<TA,TB>(d, da, db, sd);
  if constexpr (N == 32) wgmma_n32<TA,TB>(d, da, db, sd);
  if constexpr (N == 48) wgmma_n48<TA,TB>(d, da, db, sd);
  if constexpr (N == 64) wgmma_n64<TA,TB>(d, da, db, sd);
  if constexpr (N == 80) wgmma_n80<TA,TB>(d, da, db, sd);
  if constexpr (N == 96) wgmma_n96<TA,TB>(d, da, db, sd);
  if constexpr (N == 112) wgmma_n112<TA,TB>(d, da, db, sd);
  if constexpr (N == 128) wgmma_n128<TA,TB>(d, da, db, sd);
  if constexpr (N == 144) wgmma_n144<TA,TB>(d, da, db, sd);
  if constexpr (N == 160) wgmma_n160<TA,TB>(d, da, db, sd);
  if constexpr (N == 176) wgmma_n176<TA,TB>(d, da, db, sd);
  if constexpr (N == 192) wgmma_n192<TA,TB>(d, da, db, sd);
  if constexpr (N == 208) wgmma_n208<TA,TB>(d, da, db, sd);
  if constexpr (N == 224) wgmma_n224<TA,TB>(d, da, db, sd);
  if constexpr (N == 240) wgmma_n240<TA,TB>(d, da, db, sd);
  if constexpr (N == 256) wgmma_n256<TA,TB>(d, da, db, sd);
}


namespace {

constexpr int SEQ = 2048;
constexpr int DM = 640;
constexpr int NA_CTA = 80;
constexpr int NB_CTA = 52;
constexpr int NCTA = NA_CTA + NB_CTA;
constexpr int NTHREADS = 384;
constexpr int STAGE_BYTES = 49152;
constexpr int A_PART = 16384;
constexpr int SM_MISC = 7 * 32768;
constexpr int SM_POLE = SM_MISC + 304;
constexpr int SMEM_BYTES = SM_POLE + 2048 + 16 + 256;
constexpr int P0_DELAY = 1500, P_STEP = 500;
constexpr int SPLIT = 7;
constexpr int GR = 3;
constexpr int FA = 80;
constexpr int PIECE = 8192;
constexpr int CONV_TAIL = 4;
#define STG_SLOT(wg) ((wg) ? 1 : 4)
constexpr int SPIN_LIMIT = 1 << 20;
constexpr int MBAR_LIMIT = 1 << 17;

__device__ __align__(128) unsigned char g_h[8 * 20 * 2 * 16384];
__device__ __align__(128) unsigned long long g_agg[8 * DM * 2];
__device__ __align__(128) unsigned g_flag_h[320 * 8];
__device__ __align__(128) unsigned char g_ut[DM * 4096];
__device__ __align__(128) unsigned char g_yt[224 * 4096];
__device__ __align__(128) unsigned g_cnt[32 * 32];
__device__ __align__(128) unsigned g_epoch[NCTA * 32];

struct Params {
    CUtensorMap mX, mB, mC, mO, mK8, mK3, mV8, mQ8, mO8;
    const __nv_bfloat16 *lam_re, *lam_im, *c_re, *c_im, *log_dt, *dskip;
    const __nv_bfloat16 *q, *k, *v, *shift_k, *ssm_k, *ssm_d;
    float* out;
    unsigned char* h;
    unsigned long long* agg;
    unsigned char *ut, *yt;
    unsigned *flag_h, *cnt, *epoch;
    int zero;
    int swap_c;
    int swap;
};

__device__ __forceinline__ uint32_t smem_u32(const void* p) { return (uint32_t)__cvta_generic_to_shared(p); }
__device__ __forceinline__ void mbar_init(uint32_t bar, int cnt) { asm volatile("mbarrier.init.shared::cta.b64 [%0], %1;" :: "r"(bar), "r"(cnt) : "memory"); }
__device__ __forceinline__ void mbar_expect_tx(uint32_t bar, int bytes) { asm volatile("mbarrier.arrive.expect_tx.shared::cta.b64 _, [%0], %1;" :: "r"(bar), "r"(bytes) : "memory"); }
__device__ __forceinline__ void mbar_arrive(uint32_t bar) { asm volatile("mbarrier.arrive.shared::cta.b64 _, [%0];" :: "r"(bar) : "memory"); }
__device__ __forceinline__ uint32_t mapa(uint32_t addr, uint32_t cta) { uint32_t r; asm volatile("mapa.shared::cluster.u32 %0, %1, %2;" : "=r"(r) : "r"(addr), "r"(cta)); return r; }
__device__ __forceinline__ void mbar_arrive_remote(uint32_t rbar) { asm volatile("mbarrier.arrive.shared::cluster.b64 _, [%0];" :: "r"(rbar) : "memory"); }
__device__ __forceinline__ void mbar_wait(uint32_t bar, int parity) {
#pragma unroll 1
    for (int i = 0; i < MBAR_LIMIT; i++) {
        uint32_t ok;
        asm volatile("{\n.reg .pred p;\nmbarrier.try_wait.parity.shared::cta.b64 p, [%1], %2;\nselp.u32 %0, 1, 0, p;\n}" : "=r"(ok) : "r"(bar), "r"(parity) : "memory");
        if (ok) return;
    }
    __trap();
}
__device__ __forceinline__ unsigned ld_acquire(const unsigned* p) { unsigned v; asm volatile("ld.acquire.gpu.global.u32 %0, [%1];" : "=r"(v) : "l"(p) : "memory"); return v; }
__device__ __forceinline__ void st_release(unsigned* p, unsigned v) { asm volatile("st.release.gpu.global.u32 [%0], %1;" :: "l"(p), "r"(v) : "memory"); }
__device__ __forceinline__ unsigned ld_relaxed(const unsigned* p) { unsigned v; asm volatile("ld.relaxed.gpu.global.u32 %0, [%1];" : "=r"(v) : "l"(p) : "memory"); return v; }
__device__ __forceinline__ void wait_count(const unsigned* p, unsigned target) {
#pragma unroll 1
    for (int i = 0; i < SPIN_LIMIT; i++) { if ((int)(ld_acquire(p) - target) >= 0) return; }
    __trap();
}
__device__ __forceinline__ void red_release(unsigned* p, unsigned v) { asm volatile("red.release.gpu.global.add.u32 [%0], %1;" :: "l"(p), "r"(v) : "memory"); }
constexpr int GCH = 416;
constexpr int CNT_U = 0, CNT_Y = 20;
__device__ __forceinline__ void delay_until(unsigned t_start, int cyc) { while ((unsigned)clock() - t_start < (unsigned)cyc) {} }
__device__ __forceinline__ void fence_async_smem() { asm volatile("fence.proxy.async.shared::cta;" ::: "memory"); }
__device__ __forceinline__ void fence_async_global() { asm volatile("fence.proxy.async.global;" ::: "memory"); }
__device__ __forceinline__ void bar_sync(int id, int n) { asm volatile("bar.sync %0, %1;" :: "r"(id), "r"(n) : "memory"); }

__device__ __forceinline__ void tma_ld4(uint32_t dst, const CUtensorMap* m, uint32_t bar, int c0, int c1, int c2, int c3) {
    asm volatile("cp.async.bulk.tensor.4d.shared::cluster.global.mbarrier::complete_tx::bytes [%0], [%1, {%3, %4, %5, %6}], [%2];"
                 :: "r"(dst), "l"(m), "r"(bar), "r"(c0), "r"(c1), "r"(c2), "r"(c3) : "memory");
}
__device__ __forceinline__ void tma_ld5(uint32_t dst, const CUtensorMap* m, uint32_t bar, int c0, int c1, int c2, int c3, int c4) {
    asm volatile("cp.async.bulk.tensor.5d.shared::cluster.global.mbarrier::complete_tx::bytes [%0], [%1, {%3, %4, %5, %6, %7}], [%2];"
                 :: "r"(dst), "l"(m), "r"(bar), "r"(c0), "r"(c1), "r"(c2), "r"(c3), "r"(c4) : "memory");
}
__device__ __forceinline__ void tma_st3(const CUtensorMap* m, uint32_t src, int c0, int c1, int c2) {
    asm volatile("cp.async.bulk.tensor.3d.global.shared::cta.bulk_group [%0, {%2, %3, %4}], [%1];"
                 :: "l"(m), "r"(src), "r"(c0), "r"(c1), "r"(c2) : "memory");
}
__device__ __forceinline__ void tma_st5(const CUtensorMap* m, uint32_t src, int c0, int c1, int c2, int c3, int c4) {
    asm volatile("cp.async.bulk.tensor.5d.global.shared::cta.bulk_group [%0, {%2, %3, %4, %5, %6}], [%1];"
                 :: "l"(m), "r"(src), "r"(c0), "r"(c1), "r"(c2), "r"(c3), "r"(c4) : "memory");
}
__device__ __forceinline__ void bulk_st(void* dst, uint32_t src, uint32_t bytes) {
    asm volatile("cp.async.bulk.global.shared::cta.bulk_group [%0], [%1], %2;" :: "l"(dst), "r"(src), "r"(bytes) : "memory");
}
__device__ __forceinline__ void bulk_commit() { asm volatile("cp.async.bulk.commit_group;" ::: "memory"); }
__device__ __forceinline__ void bulk_wait0() { asm volatile("cp.async.bulk.wait_group 0;" ::: "memory"); }
__device__ __forceinline__ void bulk_wait0_read() { asm volatile("cp.async.bulk.wait_group.read 0;" ::: "memory"); }
__device__ __forceinline__ void prefetch_tmap(const CUtensorMap* m) { asm volatile("prefetch.tensormap [%0];" :: "l"(m) : "memory"); }


#define ELECT_OPEN "{\n.reg .pred q;\nelect.sync _|q, 0xffffffff;\n@q "
#define ELECT_CLOSE "\n}"
__device__ __forceinline__ void e_expect_tx(uint32_t bar, int bytes) { asm volatile(ELECT_OPEN "mbarrier.arrive.expect_tx.shared::cta.b64 _, [%0], %1;" ELECT_CLOSE :: "r"(bar), "r"(bytes) : "memory"); }
__device__ __forceinline__ void e_bulk_ld(uint32_t dst, const void* src, uint32_t bytes, uint32_t bar) {
    asm volatile(ELECT_OPEN "cp.async.bulk.shared::cluster.global.mbarrier::complete_tx::bytes [%0], [%1], %2, [%3];" ELECT_CLOSE :: "r"(dst), "l"(src), "r"(bytes), "r"(bar) : "memory");
}
__device__ __forceinline__ void e_tma_ld3(uint32_t dst, const CUtensorMap* m, uint32_t bar, int c0, int c2) {
    asm volatile(ELECT_OPEN "cp.async.bulk.tensor.3d.shared::cluster.global.mbarrier::complete_tx::bytes [%0], [%1, {%3, %4, %5}], [%2];" ELECT_CLOSE
                 :: "r"(dst), "l"(m), "r"(bar), "r"(c0), "r"(c2), "r"(0) : "memory");
}
__device__ __forceinline__ void e_tma_ld3x(uint32_t dst, const CUtensorMap* m, uint32_t bar, int c0, int c1, int c2) {
    asm volatile(ELECT_OPEN "cp.async.bulk.tensor.3d.shared::cluster.global.mbarrier::complete_tx::bytes [%0], [%1, {%3, %4, %5}], [%2];" ELECT_CLOSE
                 :: "r"(dst), "l"(m), "r"(bar), "r"(c0), "r"(c1), "r"(c2) : "memory");
}
__device__ __forceinline__ void e_tma_ld3_mc(uint32_t dst, const CUtensorMap* m, uint32_t bar, int c0, int c2) {
    asm volatile(ELECT_OPEN "cp.async.bulk.tensor.3d.shared::cluster.global.mbarrier::complete_tx::bytes.multicast::cluster [%0], [%1, {%3, %4, %5}], [%2], %6;" ELECT_CLOSE
                 :: "r"(dst), "l"(m), "r"(bar), "r"(c0), "r"(c2), "r"(0), "h"((uint16_t)3) : "memory");
}
__device__ __forceinline__ void e_tma_ld4(uint32_t dst, const CUtensorMap* m, uint32_t bar, int c0, int c3) {
    asm volatile(ELECT_OPEN "cp.async.bulk.tensor.4d.shared::cluster.global.mbarrier::complete_tx::bytes [%0], [%1, {%3, %4, %4, %5}], [%2];" ELECT_CLOSE
                 :: "r"(dst), "l"(m), "r"(bar), "r"(c0), "r"(0), "r"(c3) : "memory");
}
__device__ __forceinline__ void e_tma_ld5_mc(uint32_t dst, const CUtensorMap* m, uint32_t bar, int c0, int c3, int c4) {
    asm volatile(ELECT_OPEN "cp.async.bulk.tensor.5d.shared::cluster.global.mbarrier::complete_tx::bytes.multicast::cluster [%0], [%1, {%3, %4, %4, %5, %6}], [%2], %7;" ELECT_CLOSE
                 :: "r"(dst), "l"(m), "r"(bar), "r"(c0), "r"(0), "r"(c3), "r"(c4), "h"((uint16_t)3) : "memory");
}

__device__ __forceinline__ uint64_t make_desc(uint32_t addr, uint32_t lbo, uint32_t sbo, uint32_t swz) {
    return (uint64_t)((addr & 0x3FFFF) >> 4) | ((uint64_t)(lbo >> 4) << 16) | ((uint64_t)(sbo >> 4) << 32) | ((uint64_t)swz << 62);
}
#define WG_FENCE() asm volatile("wgmma.fence.sync.aligned;" ::: "memory")
#define WG_COMMIT() asm volatile("wgmma.commit_group.sync.aligned;" ::: "memory")
#define WG_WAIT(n) asm volatile("wgmma.wait_group.sync.aligned %0;" :: "n"(n) : "memory")

__device__ __forceinline__ uint32_t pack_bf16(float lo, float hi) { uint32_t r; asm("cvt.rn.bf16x2.f32 %0, %1, %2;" : "=r"(r) : "f"(hi), "f"(lo)); return r; }
__device__ __forceinline__ float bf16r(float x) { return __bfloat162float(__float2bfloat16_rn(x)); }
__device__ __forceinline__ float bf_lo(uint32_t w) { return __uint_as_float(w << 16); }
__device__ __forceinline__ float bf_hi(uint32_t w) { return __uint_as_float(w & 0xffff0000u); }
__device__ __forceinline__ float2 cmul(float2 a, float2 b) { return make_float2(a.x * b.x - a.y * b.y, a.x * b.y + a.y * b.x); }
__device__ __forceinline__ float2 cfma(float2 a, float2 b, float2 c) {
    return make_float2(fmaf(a.x, b.x, fmaf(-a.y, b.y, c.x)), fmaf(a.x, b.y, fmaf(a.y, b.x, c.y)));
}
__device__ __forceinline__ float2 lam_bar(float log_dt, float lre, float lim) {
    const float dt = bf16r(expf(log_dt));
    const float e = expf(dt * lre), x = dt * lim;
    const float k = rintf(x * 0.15915494309189535f);
    const float y = fmaf(k, 7.1054274e-15f, fmaf(k, 1.7484555e-7f, fmaf(k, -6.2831855f, x)));
    return make_float2(e * __cosf(y), e * __sinf(y));
}


__device__ __forceinline__ void bar_arrive(int id, int n) { asm volatile("bar.arrive %0, %1;" :: "r"(id), "r"(n) : "memory"); }
__device__ __forceinline__ uint4 ldg128(const void* p) {
    uint4 v; asm volatile("ld.global.nc.L2::128B.v4.u32 {%0, %1, %2, %3}, [%4];" : "=r"(v.x), "=r"(v.y), "=r"(v.z), "=r"(v.w) : "l"(p)); return v;
}
__device__ __forceinline__ uint32_t bmul(uint32_t a, uint32_t b) { uint32_t r; asm("mul.rn.bf16x2 %0, %1, %2;" : "=r"(r) : "r"(a), "r"(b)); return r; }
__device__ __forceinline__ uint32_t bfma(uint32_t a, uint32_t b, uint32_t c) { uint32_t r; asm("fma.rn.bf16x2 %0, %1, %2, %3;" : "=r"(r) : "r"(a), "r"(b), "r"(c)); return r; }
__device__ __forceinline__ uint32_t badd(uint32_t a, uint32_t b) { uint32_t r; asm("add.rn.bf16x2 %0, %1, %2;" : "=r"(r) : "r"(a), "r"(b)); return r; }

constexpr int P_BUF = 9728;
__device__ __forceinline__ void b_prep_load(const Params& P, int blk, uint32_t buf, uint32_t bar) {
    const int ch = (blk >> 5) * 32, ck = (blk & 31) * 8;
    e_expect_tx(bar, P_BUF);
    e_tma_ld3x(buf + 1536, &P.mK8, bar, ch, ck, 0);
    e_tma_ld3x(buf + 5632, &P.mV8, bar, ch, ck, 0);
    e_tma_ld3x(buf, &P.mK3, bar, ch, ck - 1, 5);
}
__device__ __forceinline__ void b_prep(const Params& P, int blk, int lane, uint32_t buf, uint32_t bar, int parity, unsigned char* sm) {
    const int ch0 = (blk >> 5) * 32 + (lane & 3) * 8, t0 = (blk & 31) * 64 + (lane >> 2) * 8;
    uint4 sw[4];
#pragma unroll
    for (int i = 0; i < 4; i++) sw[i] = ldg128(P.shift_k + ch0 * 4 + i * 8);
    mbar_wait(bar, parity);
    const uint4* src = (const uint4*)(sm + (buf - smem_u32(sm))) + lane;
    unsigned char* dst = P.ut + ch0 * 4096 + (255 - (t0 >> 3)) * 16;
    uint32_t w[4][4], u[8][4];
#pragma unroll
    for (int cp = 0; cp < 4; cp++) {
        w[0][cp] = __byte_perm(sw[cp].x, sw[cp].z, 0x5410); w[1][cp] = __byte_perm(sw[cp].x, sw[cp].z, 0x7632);
        w[2][cp] = __byte_perm(sw[cp].y, sw[cp].w, 0x5410); w[3][cp] = __byte_perm(sw[cp].y, sw[cp].w, 0x7632);
    }
    uint4 kk[11];
#pragma unroll
    for (int i = 0; i < 3; i++) kk[i] = src[i * 32];
#pragma unroll
    for (int i = 0; i < 8; i++) {
        kk[i + 3] = src[(i + 3) * 32];
        const uint4 vv = src[352 + i * 32];
#pragma unroll
        for (int cp = 0; cp < 4; cp++) {
            const uint32_t acc = badd(badd(badd(bmul(((const uint32_t*)&kk[i])[cp], w[3][cp]), bmul(((const uint32_t*)&kk[i + 1])[cp], w[2][cp])),
                                           bmul(((const uint32_t*)&kk[i + 2])[cp], w[1][cp])), bmul(((const uint32_t*)&kk[i + 3])[cp], w[0][cp]));
            u[i][cp] = bmul(acc, ((const uint32_t*)&vv)[cp]);
        }
    }
#pragma unroll
    for (int cp = 0; cp < 4; cp++) {
        *(uint4*)(dst + (2 * cp) * 4096) = make_uint4(__byte_perm(u[0][cp], u[1][cp], 0x5410), __byte_perm(u[2][cp], u[3][cp], 0x5410), __byte_perm(u[4][cp], u[5][cp], 0x5410), __byte_perm(u[6][cp], u[7][cp], 0x5410));
        *(uint4*)(dst + (2 * cp + 1) * 4096) = make_uint4(__byte_perm(u[0][cp], u[1][cp], 0x7632), __byte_perm(u[2][cp], u[3][cp], 0x7632), __byte_perm(u[4][cp], u[5][cp], 0x7632), __byte_perm(u[6][cp], u[7][cp], 0x7632));
    }
}

__device__ __forceinline__ void b_prep_block(const Params& P, int blk, int lane, uint32_t buf, uint32_t bar, int parity, unsigned char* sm) {
    b_prep_load(P, blk, buf, bar);
    b_prep(P, blk, lane, buf, bar, parity, sm);
    fence_async_global();
    __syncwarp();
    if (lane == 0) red_release(&P.cnt[(CNT_U + (blk >> 5)) * 32], 1);
    __syncwarp();
}

__device__ __forceinline__ void b_final(const Params& P, int blk, int lane, unsigned epoch) {
    const int cg = blk >> 5, chq = GCH + cg * 32 + (lane & 7) * 4, t0 = (blk & 31) * 64 + (lane >> 3) * 8;
    const unsigned char* yp = P.yt + (chq - GCH) * 4096 + (t0 & 8) * 256 + (t0 >> 4) * 16;
    uint2 qq[2][8];
    uint4 yy[8];
#pragma unroll
    for (int hq = 0; hq < 2; hq++)
#pragma unroll
        for (int i = 0; i < 8; i++) qq[hq][i] = __ldg((const uint2*)(P.q + (t0 + 32 * hq + i) * DM + chq));
    wait_count(&P.cnt[(CNT_Y + cg) * 32], (epoch + 1) * 128);
#pragma unroll
    for (int z = 0; z < 8; z++) yy[z] = __ldcg((const uint4*)(yp + (z & 3) * 4096 + (z >> 2) * 32));
#pragma unroll
    for (int hq = 0; hq < 2; hq++)
#pragma unroll
        for (int i = 0; i < 8; i++) {
            const uint32_t sel = (i & 1) ? 0x7632 : 0x5410;
            const uint32_t a = bmul(__byte_perm(((const uint32_t*)&yy[4 * hq])[i >> 1], ((const uint32_t*)&yy[4 * hq + 1])[i >> 1], sel), qq[hq][i].x);
            const uint32_t b = bmul(__byte_perm(((const uint32_t*)&yy[4 * hq + 2])[i >> 1], ((const uint32_t*)&yy[4 * hq + 3])[i >> 1], sel), qq[hq][i].y);
            *(float4*)(P.out + (t0 + 32 * hq + i) * 1280 + DM + chq) = make_float4(bf_lo(a), bf_hi(a), bf_lo(b), bf_hi(b));
        }
}

__device__ __forceinline__ unsigned take_epoch(const Params& P, unsigned char* sm, int lane) {
    unsigned e;
    asm volatile("ld.global.u32 %0, [%1];" : "=r"(e) : "l"(&P.epoch[blockIdx.x * 32 + lane]) : "memory");
    P.epoch[blockIdx.x * 32 + lane] = e + 1;
    if (lane == 0) *(volatile unsigned*)(sm + SM_POLE + 2048) = e;
    return e;
}
__device__ __forceinline__ unsigned smem_epoch(unsigned char* sm) { return *(volatile unsigned*)(sm + SM_POLE + 2048); }

constexpr int B_UH = 8448;
constexpr int B_PLANE = 4128;
constexpr int B_LEFT = 4 * B_PLANE;
constexpr int B_RED = B_LEFT + 1280;
constexpr int B_WG = 3 * B_UH + 2 * B_RED;
constexpr int B_PBUF = 2 * B_WG;
constexpr int B_Q = B_PBUF, B_O = B_Q + 32768, B_Y = B_O + 32768;
constexpr int BB_Q = 256;
constexpr int BB_RDY = 0, BB_FREE = 32, BB_ROWS = 64, BB_GATE = 96, BB_EPOCH = 104, BB_FULL = 112, BB_PREP = 160;
static_assert(B_UH % 128 == 0 && B_RED % 128 == 0 && B_PBUF % 128 == 0 && B_PBUF % 1024 == 0 && B_Y + 8 * 4224 <= SM_MISC && 4 * P_BUF <= 65536 && B_UH + 4 * P_BUF <= B_WG, "layout");

template<int S> __device__ __forceinline__ void conv_mma(float* d, uint64_t da, uint64_t db, int zero) {
    if (S > 0) WG_FENCE();
    wgmma_ss<256 - 16 * S, 1, 1>(d, da + S * 16, db + S * 16, S > 0 ? 1 : zero);
    WG_COMMIT();
    if constexpr (S + 1 < 16) conv_mma<S + 1>(d, da, db, zero);
}
__device__ __forceinline__ int b_channel(int b, int wg, int m) {
    if (wg == 0 || b < 12) { if (m == GR) return GCH + 160 + 52 * wg + b; if (m > GR) m--; }
    return 8 * b + 2 * m + wg;
}

__device__ __forceinline__ void patch_tap0(unsigned char* hrow, __nv_bfloat16 dd) {
    __nv_bfloat16* p = (__nv_bfloat16*)(hrow + 112);
    *p = __float2bfloat16_rn(__bfloat162float(*p) + __bfloat162float(dd));
    fence_async_smem();
}
__device__ __forceinline__ void conv_fold(const float* d, uint32_t p01, uint32_t p23, int wx, int lane) {
    const int m7 = lane & 7, mi = lane >> 3, g = lane >> 2;
    const uint32_t st = ((m7 & 4) ? p23 : p01) + ((m7 >> 1) & 1) * B_PLANE + 16 + ((m7 & 1) ? 0 : 2064) + (4 * (31 - mi) + wx) * 16;
    const uint32_t sel = g ? 0x3210u : 0x1044u;
    uint32_t x[32];
#pragma unroll
    for (int z = 0; z < 32; z++) x[z] = __shfl_sync(~0u, pack_bf16(d[4 * z + 1], d[4 * z + 3]), (lane - 4) & 31);
#pragma unroll
    for (int q = 0; q < 8; q++) {
        uint32_t rr[4];
#pragma unroll
        for (int z = 0; z < 4; z++) rr[z] = badd(pack_bf16(d[16 * q + 4 * z], d[16 * q + 4 * z + 2]), __byte_perm(x[4 * q + z], 0, sel));
        asm volatile("stmatrix.sync.aligned.m8n8.x4.trans.shared.b16 [%0], {%1, %2, %3, %4};" :: "r"(st - q * 256), "r"(rr[0]), "r"(rr[1]), "r"(rr[2]), "r"(rr[3]) : "memory");
    }
    if (g == 0) {
        const uint32_t lo = p23 + 2 * B_PLANE + wx * 288 + lane * 64;
#pragma unroll
        for (int q = 0; q < 4; q++)
            asm volatile("st.shared.v4.u32 [%0], {%1, %2, %3, %4};" :: "r"(lo + q * 16), "r"(__byte_perm(x[8 * q], x[8 * q + 1], 0x7632)), "r"(__byte_perm(x[8 * q + 2], x[8 * q + 3], 0x7632)),
                         "r"(__byte_perm(x[8 * q + 4], x[8 * q + 5], 0x7632)), "r"(__byte_perm(x[8 * q + 6], x[8 * q + 7], 0x7632)) : "memory");
    }
}
__device__ __forceinline__ void conv_sum(unsigned char* yrow, int odd, uint32_t p01, uint32_t p23, int tl, uint32_t free_bar) {
    uint32_t w[4][12];
    uint16_t lv[4];
    const uint32_t lo = p23 + 2 * B_PLANE + ((tl - 1) & 3) * 288 + (31 - ((tl - 1) >> 2)) * 2;
#pragma unroll
    for (int e = 0; e < 4; e++) {
        const uint32_t pa = (e & 2 ? p23 : p01) + (e & 1) * B_PLANE + tl * 16;
        if (e > 0) asm volatile("ld.shared.v4.u32 {%0, %1, %2, %3}, [%4];" : "=r"(w[e][0]), "=r"(w[e][1]), "=r"(w[e][2]), "=r"(w[e][3]) : "r"(pa) : "memory");
        asm volatile("ld.shared.v4.u32 {%0, %1, %2, %3}, [%4];" : "=r"(w[e][4]), "=r"(w[e][5]), "=r"(w[e][6]), "=r"(w[e][7]) : "r"(pa + 2080) : "memory");
        asm volatile("ld.shared.v4.u32 {%0, %1, %2, %3}, [%4];" : "=r"(w[e][8]), "=r"(w[e][9]), "=r"(w[e][10]), "=r"(w[e][11]) : "r"(pa + 16) : "memory");
        lv[e] = 0;
        if (tl > 0) asm volatile("ld.shared.u16 %0, [%1];" : "=h"(lv[e]) : "r"(lo + e * 64) : "memory");
    }
    uint32_t yo[8];
#pragma unroll
    for (int z = 0; z < 8; z++) {
        float y0 = (bf_lo(w[0][4 + z]) + bf_lo(w[1][3 + z])) + (bf_lo(w[2][2 + z]) + bf_lo(w[3][1 + z]));
        const float y1 = (bf_hi(w[0][4 + z]) + bf_hi(w[1][3 + z])) + (bf_hi(w[2][2 + z]) + bf_hi(w[3][1 + z]));
        if (z < 4) y0 += __uint_as_float((uint32_t)lv[z] << 16);
        yo[z] = pack_bf16(y0, y1);
    }
    if (free_bar) { __syncwarp(); if ((tl & 31) == 0) mbar_arrive(free_bar); }
    uint4* dst = (uint4*)yrow + tl;
    dst[0] = make_uint4(yo[0], yo[1], yo[2], yo[3]);
    dst[odd] = make_uint4(yo[4], yo[5], yo[6], yo[7]);
}


constexpr int BAR_FULL1 = 0, BAR_EMPTY1 = 32, BAR_FULL2 = 64, BAR_EMPTY2 = 120, BAR_HREADY = 176, BAR_HSTORED = 208, BAR_HOSTF1 = 216, BAR_OWNC = 224, BAR_POLE = 232, BAR_HSTORED_B = 240, BAR_GO2 = 272, BAR_HOSTF = 280, BAR_HOSTD = 288;
constexpr int HOST_P01 = B_UH, HOST_P23 = HOST_P01 + 2 * B_PLANE;
#define HOST_UH(wg) ((wg) ? 0 : 2 * 32768)
constexpr int SLOT2 = 32768;
__host__ __device__ constexpr int ring_slot(int i) { return (0x630254 >> (4 * i)) & 7; }
__device__ __forceinline__ int g2_kb(int e, int j, int r) {
    const int w = e >= 9, i = e - 9 * w, g = j + 1 + (i >> 1);
    return 2 * (i < 8 ? (g >= 5 ? g - 5 : g) + 5 * (i & 1) : j + 5 * (1 - r)) + w;
}
#define A_COORDS \
    const int cl = (blockIdx.x - NB_CTA) >> 1, r = blockIdx.x & 1; \
    const int c = cl / 5, j = cl % 5, pg = j + 5 * r;       \
    const uint32_t bars = sb + SM_MISC

__device__ __forceinline__ void a_poles(const Params& P, unsigned char* sm, uint32_t sb, int w, int lane) {
    A_COORDS;
    (void)c;
    if (w == 0) take_epoch(P, sm, lane);
    if (w == 1 && lane == 0) *(uint32_t*)(sm + SM_POLE + 2052) = *(const uint32_t*)(P.ssm_d + GCH + 2 * (blockIdx.x - NB_CTA));
    const int p = 64 * pg + 32 * w + lane;
    const float lx = __bfloat162float(P.lam_re[p]), ly = __bfloat162float(P.lam_im[p]);
    float2 L1 = lam_bar(__bfloat162float(P.log_dt[p]), lx, ly);
    const float nr = L1.x - 1.f, ni = L1.y, den = lx * lx + ly * ly;
    const float cr = 2.f * (nr * lx + ni * ly) / den, ci = 2.f * (ni * lx - nr * ly) / den;
    float4 om = P.swap ? make_float4(-ci, cr, -cr, -ci) : make_float4(cr, -ci, -ci, -cr);
    if (P.swap_c) om = make_float4(om.z, om.w, om.x, om.y);
    if (P.swap) L1.y = -L1.y;
    float2 L16 = L1;
#pragma unroll
    for (int i = 0; i < 4; i++) L16 = cmul(L16, L16);
    *(float4*)(sm + SM_POLE + (32 * w + lane) * 32) = make_float4(L1.x, L1.y, L16.x, L16.y);
    *(float4*)(sm + SM_POLE + (32 * w + lane) * 32 + 16) = om;
    *(uint32_t*)(sm + SM_POLE + 2064 + (32 * w + lane) * 4) = *(const uint32_t*)(P.dskip + j * 128 + (32 * w + lane) * 2);
    __syncwarp();
    if (lane == 0) mbar_arrive(bars + BAR_POLE);
}

__device__ __forceinline__ void a_aux(const Params& P, unsigned char* sm, uint32_t sb, int warp, int lane) {
    A_COORDS;
    if (warp == 8) {
#pragma unroll
        for (int it = 4; it < 10; it++) {
            const int s = it & 3;
            const uint32_t st = sb + s * STAGE_BYTES, fb = bars + BAR_FULL1 + s * 8;
            mbar_wait(bars + BAR_EMPTY1 + s * 8, ((it >> 2) - 1) & 1);
            e_expect_tx(fb, STAGE_BYTES);
            e_tma_ld4(st, &P.mB, fb, it * 64, 8 * pg);
            e_tma_ld5_mc(st + A_PART + r * 16384, &P.mX, fb, it * 64, 16 * r, c);
        }
        if (lane == 0) mbar_arrive(bars + BAR_GO2);
        mbar_wait(bars + BAR_POLE, 0);
        const unsigned tag = ~smem_epoch(sm);
        wait_count(&P.cnt[(CNT_U + ((GCH + 2 * (blockIdx.x - NB_CTA)) >> 5)) * 32], (~tag + 1) * 32);
        fence_async_global();
        mbar_wait(bars + BAR_EMPTY1 + 8, 0);
#pragma unroll 1
        for (int w = 0; w < 2; w++) {
            const int ch = GCH + 2 * (blockIdx.x - NB_CTA) + w;
            const uint32_t fb = bars + (w ? BAR_HOSTF1 : BAR_HOSTF);
            e_expect_tx(fb, 8192);
            e_bulk_ld(sb + HOST_UH(w) + 4224 + 112, P.ssm_k + ch * SEQ, 4096, fb);
            e_bulk_ld(sb + HOST_UH(w), P.ut + ch * 4096, 4096, fb);
        }
        const int mykb = g2_kb(lane < 18 ? lane : 0, j, r);
        const unsigned* fp = &P.flag_h[((c * 20 + mykb) * 2 + r) * 8];
        const unsigned char* h_c = P.h + (c * 40 + r) * 16384;
        unsigned ready = 0;
#pragma unroll 1
        for (int o = 0; o < 3; o++) {
#pragma unroll
            for (int i = 0; i < 6; i++) {
                const int e = 6 * o + i;
                if (!((ready >> e) & 1)) {
                    int spin = 0;
                    do {
                        ready = __ballot_sync(~0u, lane < 18 && ld_relaxed(fp) == tag);
                        if (++spin > SPIN_LIMIT) __trap();
                    } while (!((ready >> e) & 1));
                    fence_async_global();
                }
                const unsigned char* src = h_c + g2_kb(e, j, r) * 32768;
                if (i >= 2 || o) mbar_wait(bars + BAR_EMPTY2 + i * 8, (i < 2 ? o - 1 : o) & 1);
                e_bulk_ld(sb + ring_slot(i) * SLOT2 + 16384, src, 16384, bars + BAR_FULL2 + i * 8);
            }
        }
    } else if (warp == 11) {
        mbar_wait(bars + BAR_GO2, 0);
        mbar_wait(bars + BAR_EMPTY1 + 16, 1);
        e_expect_tx(bars + BAR_OWNC, SLOT2);
#pragma unroll 1
        for (int q = 0; q < 4; q++) e_tma_ld3(sb + 3 * SLOT2 + q * 8192, &P.mC, bars + BAR_OWNC, (2 * pg + (q >> 1)) * 32, j * 128 + (q & 1) * 64);
        mbar_wait(bars + BAR_EMPTY1 + 24, 1);
#pragma unroll 1
        for (int o = 0; o < 3; o++) {
#pragma unroll
            for (int i = 0; i < 6; i++) {
                const int e = 6 * o + i, kc = g2_kb(e, j, r) * 32;
                const uint32_t st = sb + ring_slot(i) * SLOT2, fb = bars + BAR_FULL2 + i * 8;
                if (i >= 2 || o) mbar_wait(bars + BAR_EMPTY2 + i * 8, (i < 2 ? o - 1 : o) & 1);
                e_expect_tx(fb, SLOT2);
                if ((i != 2 && i != 5) || (e != 8 && e != 17)) e_tma_ld3_mc(st + r * 8192, &P.mC, fb, kc, j * 128 + r * 64);
                else { e_tma_ld3(st, &P.mC, fb, kc, j * 128); e_tma_ld3(st + 8192, &P.mC, fb, kc, j * 128 + 64); }
            }
        }
    } else {
        const int w = warp - 9;
        mbar_wait(bars + BAR_POLE, 0);
        const unsigned epoch = smem_epoch(sm);
        if (lane == 0) {
            unsigned* fl = &P.flag_h[((c * 20 + 2 * pg) * 2 + w) * 8];
#pragma unroll 1
            for (int g2 = 0; g2 < 2; g2++) {
                mbar_wait(bars + BAR_HREADY + g2 * 16 + w * 8, 0);
                unsigned char* dst = P.h + ((c * 20 + 2 * pg + g2) * 2 + w) * 16384;
                const uint32_t src = sb + (g2 ? 1 : 6) * SLOT2 + w * 16384;
                const int piece = g2 ? PIECE : 16384;
#pragma unroll 1
                for (int o = 0; o < 16384; o += piece) {
                    bulk_st(dst + o, src + o, piece);
                    bulk_commit();
                    bulk_wait0();
                }
                mbar_arrive(bars + (g2 ? BAR_HSTORED_B : BAR_HSTORED));
                fence_async_global();
                st_release(fl + 16 * g2, ~epoch);
            }
            if (w == 1) {
                mbar_wait(bars + BAR_HOSTD, 0);
                red_release(&P.cnt[(CNT_Y + ((blockIdx.x - NB_CTA) >> 4)) * 32], 8);
            }
        }
        __syncwarp();
    }
}

__device__ __forceinline__ void a_first(const Params& P, uint32_t* xm, unsigned char* sm, uint32_t sb, int warp, int lane) {
    A_COORDS;
    const int wg = warp >> 2, wx = warp & 3, g = lane >> 2, t = lane & 3;
    const int p = 64 * pg + 32 * wg + 8 * wx + g;
    const uint32_t rbars = mapa(bars, r ^ 1);
    unsigned long long* agg = P.agg + p * 2;
    float d[128];

#pragma unroll
    for (int seg = 0; seg < 2; seg++) {
        if (seg == 1 && wg == 1) bar_sync(1, 256);
#pragma unroll 1
        for (int it = seg * SPLIT; it < (seg ? 10 : SPLIT); it++) {
            const int s = it & 3;
            mbar_wait(bars + BAR_FULL1 + s * 8, (it >> 2) & 1);
            const uint32_t st = sb + s * STAGE_BYTES;
            const uint64_t da = make_desc(st + wg * 8192, 16, 1024, 1), db = make_desc(st + A_PART, 16, 1024, 1);
            WG_FENCE();
#pragma unroll
            for (int ks = 0; ks < 4; ks++) wgmma_ss<256, 0, 0>(d, da + 2 * ks, db + 2 * ks, (it | ks) != 0);
            WG_COMMIT();
            if (it == 9 && wg == 0) bar_arrive(1, 256);
            if (it == 2 * j + wg) {
                const int mrow = lane & 7, mi = lane >> 3;
                const uint32_t xb = st + A_PART + r * 16384 + ((mi >> 1) * 8 + mrow) * 128 + (((2 * wx + (mi & 1)) ^ mrow) << 4);
#pragma unroll
                for (int q2 = 0; q2 < 8; q2++)
                    asm volatile("ldmatrix.sync.aligned.m8n8.x4.trans.shared.b16 {%0, %1, %2, %3}, [%4];"
                                 : "=r"(xm[4 * q2]), "=r"(xm[4 * q2 + 1]), "=r"(xm[4 * q2 + 2]), "=r"(xm[4 * q2 + 3]) : "r"(xb + q2 * 2048) : "memory");
            }
            WG_WAIT(1);
            if (it != seg * SPLIT) {
                if (lane == 0) mbar_arrive(bars + BAR_EMPTY1 + ((it - 1) & 3) * 8);
                if (lane == 1) mbar_arrive_remote(rbars + BAR_EMPTY1 + ((it - 1) & 3) * 8);
            }
        }
        WG_WAIT(0);
        if (lane == 0) mbar_arrive(bars + BAR_EMPTY1 + (((seg ? 10 : SPLIT) - 1) & 3) * 8);
        if (lane == 1) mbar_arrive_remote(rbars + BAR_EMPTY1 + (((seg ? 10 : SPLIT) - 1) & 3) * 8);
    }

    mbar_wait(bars + BAR_POLE, 0);
    const float4 pole = *(const float4*)(sm + SM_POLE + (32 * wg + 8 * wx + g) * 32), om = *(const float4*)(sm + SM_POLE + (32 * wg + 8 * wx + g) * 32 + 16);
    const unsigned tag = ~smem_epoch(sm);
    const float2 L1 = make_float2(pole.x, pole.y), L16 = make_float2(pole.z, pole.w);
    float2 S[4];
#pragma unroll
    for (int z = 0; z < 4; z++) S[z] = make_float2(d[32 * z], d[32 * z + 2]);
#pragma unroll
    for (int q = 1; q < 16; q++)
#pragma unroll
        for (int z = 0; z < 4; z++) {
            const int ix = 32 * z + 4 * (q >> 1) + (q & 1);
            S[z] = cfma(L1, S[z], make_float2(d[ix], d[ix + 2]));
        }
    float2 v = cfma(L16, cfma(L16, cfma(L16, S[0], S[1]), S[2]), S[3]);
    const float2 L32 = cmul(L16, L16), L64 = cmul(L32, L32), L128 = cmul(L64, L64), L256 = cmul(L128, L128);
    {
        float2 u = make_float2(__shfl_up_sync(~0u, v.x, 1), __shfl_up_sync(~0u, v.y, 1));
        if (t >= 1) v = cfma(L64, u, v);
        u = make_float2(__shfl_up_sync(~0u, v.x, 2), __shfl_up_sync(~0u, v.y, 2));
        if (t >= 2) v = cfma(L128, u, v);
    }
    if (t == 3 && c < 7) {
        unsigned long long w0 = ((unsigned long long)tag << 32) | __float_as_uint(v.x), w1 = ((unsigned long long)tag << 32) | __float_as_uint(v.y);
        asm volatile("st.relaxed.gpu.global.v2.u64 [%0], {%1, %2};" :: "l"(agg + c * (DM * 2)), "l"(w0), "l"(w1) : "memory");
    }
    float2 h = make_float2(__shfl_up_sync(~0u, v.x, 1), __shfl_up_sync(~0u, v.y, 1));
    if (t == 0) h = make_float2(0.f, 0.f);
    if (c > 0) {
        const unsigned long long* a0p = agg + t * (DM * 2);
        const bool n0 = t < c, n1 = t + 4 < c;
        unsigned long long a0 = 0, a1 = 0, b0 = 0, b1 = 0;
        if (n0) asm volatile("ld.relaxed.gpu.global.v2.u64 {%0, %1}, [%2];" : "=l"(a0), "=l"(a1) : "l"(a0p) : "memory");
        if (n1) asm volatile("ld.relaxed.gpu.global.v2.u64 {%0, %1}, [%2];" : "=l"(b0), "=l"(b1) : "l"(a0p + 4 * DM * 2) : "memory");
        float2 w1 = make_float2(1.f, 0.f), w0 = w1;
        for (int m = c - 1 - t; m > 0; m--) { w0 = cmul(w0, L256); if (m > 4) w1 = cmul(w1, L256); }
        int spin = 0;
        while (true) {
            const bool ok0 = !n0 || ((unsigned)(a0 >> 32) == tag && (unsigned)(a1 >> 32) == tag);
            const bool ok1 = !n1 || ((unsigned)(b0 >> 32) == tag && (unsigned)(b1 >> 32) == tag);
            if (ok0 && ok1) break;
            if (!ok0) asm volatile("ld.relaxed.gpu.global.v2.u64 {%0, %1}, [%2];" : "=l"(a0), "=l"(a1) : "l"(a0p) : "memory");
            if (!ok1) asm volatile("ld.relaxed.gpu.global.v2.u64 {%0, %1}, [%2];" : "=l"(b0), "=l"(b1) : "l"(a0p + 4 * DM * 2) : "memory");
            if (++spin > SPIN_LIMIT) __trap();
        }
        float2 acc = make_float2(0.f, 0.f);
        if (n0) acc = cmul(w0, make_float2(__uint_as_float((unsigned)a0), __uint_as_float((unsigned)a1)));
        if (n1) acc = cfma(w1, make_float2(__uint_as_float((unsigned)b0), __uint_as_float((unsigned)b1)), acc);
        __syncwarp();
        acc.x += __shfl_xor_sync(~0u, acc.x, 1); acc.y += __shfl_xor_sync(~0u, acc.y, 1);
        acc.x += __shfl_xor_sync(~0u, acc.x, 2); acc.y += __shfl_xor_sync(~0u, acc.y, 2);
        float2 wt = (t & 1) ? L64 : make_float2(1.f, 0.f);
        if (t & 2) wt = cmul(wt, L128);
        h = cfma(wt, acc, h);
    }
    if (wg == 1) bar_sync(3, 128);
    {
        const uint32_t o2[4] = {pack_bf16(om.x, om.x), pack_bf16(om.y, om.y), pack_bf16(om.z, om.z), pack_bf16(om.w, om.w)};
        float2 hs[4];
        hs[0] = h; hs[1] = cfma(L16, hs[0], S[0]); hs[2] = cfma(L16, hs[1], S[1]); hs[3] = cfma(L16, hs[2], S[2]);
        const int mrow = lane & 7, mi = lane >> 3;
        const uint32_t rowaddr = sb + (wg ? 1 : 6) * SLOT2 + (32 * (mi >> 1) + 8 * wx + mrow) * 128;
#pragma unroll
        for (int cp = 0; cp < 4; cp++) {
#pragma unroll
            for (int nb = 0; nb < 4; nb++) {
                uint32_t m[4];
#pragma unroll
                for (int z = 0; z < 2; z++) {
                    const int ix = 32 * nb + 8 * cp + 4 * z;
                    const float2 h0 = cfma(L1, hs[nb], make_float2(d[ix], d[ix + 2]));
                    hs[nb] = cfma(L1, h0, make_float2(d[ix + 1], d[ix + 3]));
                    const uint32_t X = pack_bf16(h0.x, hs[nb].x), Y = pack_bf16(h0.y, hs[nb].y);
                    m[z] = bfma(X, o2[0], bmul(Y, o2[1]));
                    m[2 + z] = bfma(X, o2[2], bmul(Y, o2[3]));
                }
                const uint32_t addr = rowaddr + nb * 8192 + (((2 * cp + (mi & 1)) ^ mrow) << 4);
                asm volatile("stmatrix.sync.aligned.m8n8.x4.shared.b16 [%0], {%1, %2, %3, %4};" :: "r"(addr), "r"(m[0]), "r"(m[1]), "r"(m[2]), "r"(m[3]) : "memory");
            }
        }
        fence_async_smem();
        __syncwarp();
        if (lane < 2) mbar_arrive(bars + BAR_HREADY + wg * 16 + lane * 8);
    }
}

__device__ __forceinline__ void a_second(const Params& P, const uint32_t* xm, unsigned char* sm, uint32_t sb, int warp, int lane) {
    A_COORDS;
    const int wg = warp >> 2, wx = warp & 3, g = lane >> 2, t = lane & 3;
    (void)pg;
    float d[64];
    const uint32_t rbars = mapa(bars, r ^ 1);
    {
        const unsigned short* dk = (const unsigned short*)(sm + SM_POLE + 2064) + 64 * wg + 16 * wx + g;
        const uint32_t k0 = dk[0] * 0x10001u, k1 = dk[8] * 0x10001u;
#pragma unroll
        for (int z = 0; z < 32; z++) { const uint32_t w = bmul(xm[z], (z & 1) ? k1 : k0); d[2 * z] = bf_lo(w); d[2 * z + 1] = bf_hi(w); }
    }
#pragma unroll
    for (int z = 0; z < 64; z++) asm volatile("" : "+f"(d[z]) :: "memory");
    if (lane < 2) mbar_arrive(bars + BAR_EMPTY2 + (2 + lane) * 8);
    else if (lane < 4) mbar_arrive_remote(rbars + BAR_EMPTY2 + lane * 8);
    mbar_wait(bars + BAR_OWNC, 0);
#pragma unroll
    for (int kb = 0; kb < 2; kb++) {
        mbar_wait(bars + BAR_HREADY + kb * 16 + r * 8, 0);
        const uint64_t da = make_desc(sb + 3 * SLOT2 + kb * 16384 + wg * 8192, 16, 512, 2), db = make_desc(sb + (kb ? 1 : 6) * SLOT2 + r * 16384, 8192, 1024, 1);
        WG_FENCE();
#pragma unroll
        for (int ks = 0; ks < 4; ks++) wgmma_ss<128, 0, 1>(d, da + 256 * (ks >> 1) + 2 * (ks & 1), db + 128 * ks, 1);
        WG_COMMIT();
    }
    {
        int i = 0, u = 0;
#pragma unroll 1
        for (int e = 0; e < 18; e++) {
            mbar_wait(bars + BAR_FULL2 + i * 8, u);
            const uint32_t st = sb + ((0x1630254 >> (4 * i)) & 7) * SLOT2;
            const uint64_t da = make_desc(st + wg * 8192, 16, 512, 2), db = make_desc(st + 16384, 8192, 1024, 1);
            WG_FENCE();
#pragma unroll
            for (int ks = 0; ks < 4; ks++) wgmma_ss<128, 0, 1>(d, da + 256 * (ks >> 1) + 2 * (ks & 1), db + 128 * ks, 1);
            WG_COMMIT();
            WG_WAIT(1);
            if (e == 0) {
                mbar_wait(bars + BAR_HSTORED, 0);
                if (lane < 2) mbar_arrive(bars + BAR_EMPTY2 + (4 + lane) * 8);
                else if (lane < 4) mbar_arrive_remote(rbars + BAR_EMPTY2 + (2 + lane) * 8);
            } else if (e <= 13) {
                const int ip = i == 0 ? 5 : i - 1;
                if (lane == 0) mbar_arrive(bars + BAR_EMPTY2 + ip * 8);
                if (lane == 1) mbar_arrive_remote(rbars + BAR_EMPTY2 + ip * 8);
            }
            if (++i == 6) { i = 0; u ^= 1; }
        }
    }
    mbar_wait(bars + (wg ? BAR_HSTORED_B : BAR_EMPTY2), 0);
    WG_WAIT(0);
    {
        const uint32_t ob = sb + STG_SLOT(wg) * SLOT2 + (wx >> 1) * 16384 + (g & 3) * 4 + 2 * t * 128;
        const int ch0 = 4 * (wx & 1) + (g >> 2);
        const uint32_t o00 = ob + ((ch0 ^ (2 * t)) << 4), o01 = ob + 128 + ((ch0 ^ (2 * t + 1)) << 4);
        const uint32_t o10 = ob + (((ch0 + 2) ^ (2 * t)) << 4), o11 = ob + 128 + (((ch0 + 2) ^ (2 * t + 1)) << 4);
#pragma unroll
        for (int q = 0; q < 16; q++) {
            asm volatile("st.shared.f32 [%0], %1;" :: "r"(o00 + q * 1024), "f"(d[4 * q]));
            asm volatile("st.shared.f32 [%0], %1;" :: "r"(o01 + q * 1024), "f"(d[4 * q + 1]));
            asm volatile("st.shared.f32 [%0], %1;" :: "r"(o10 + q * 1024), "f"(d[4 * q + 2]));
            asm volatile("st.shared.f32 [%0], %1;" :: "r"(o11 + q * 1024), "f"(d[4 * q + 3]));
        }
    }
    fence_async_smem();
    bar_sync(8 + (warp >> 1), 64);
    if ((warp & 1) == 0 && lane == 0) {
        tma_st5(&P.mO, sb + STG_SLOT(wg) * SLOT2 + (wx >> 1) * 16384, j * 128 + (warp >> 1) * 32, 0, 0, 16 * r, c);
        bulk_commit();
        bulk_wait0_read();
    }
    __syncwarp();
}

__device__ __forceinline__ void b_load(const Params& P, uint32_t sb, int b, int wg, int m, unsigned epoch) {
    const int ch = b_channel(b, wg, m), buf = m % 3;
    const uint32_t dst = sb + wg * B_WG + buf * B_UH, fb = sb + SM_MISC + BB_FULL + (wg * 3 + buf) * 8;
    e_expect_tx(fb, 8192);
    e_bulk_ld(dst + 4224 + 112, P.ssm_k + ch * SEQ, 4096, fb);
    wait_count(&P.cnt[(CNT_U + (ch >> 5)) * 32], (epoch + 1) * 32);
    fence_async_global();
    e_bulk_ld(dst, P.ut + ch * 4096, 4096, fb);
}

__device__ __forceinline__ void b_aux(const Params& P, unsigned char* sm, uint32_t sb, int warp, int lane) {
    const int b = blockIdx.x, wx = warp & 3, tl = 32 * wx + lane;
    const uint32_t bars = sb + SM_MISC;
    const int nch = b < 12 ? 10 : 9;
    mbar_wait(bars + BB_EPOCH, 0);
    const unsigned epoch = smem_epoch(sm);
    mbar_wait(bars + BB_GATE, 0);
#pragma unroll 1
    for (int i = -4; i < nch; i++) {
        const int wg = i & 1, m = i >> 1, buf = m & 1, ch = b_channel(b, wg, m);
        const uint32_t red = sb + wg * B_WG + 3 * B_UH + buf * B_RED;
        if (i >= 0) mbar_wait(bars + BB_RDY + (wg * 2 + buf) * 8, (m >> 1) & 1);
        if (wx == ((i + 6) & 3) && i + 6 < nch) b_load(P, sb, b, wg, m + 3, epoch);
        if (i == 1) {
            bar_sync(5, 128);
            if (wx == 0) e_expect_tx(bars + BB_Q, 32768);
            e_tma_ld3x(sb + B_Q + wx * 8192, &P.mQ8, bars + BB_Q, b * 8, wx * 64, 0);
            e_tma_ld3x(sb + B_Q + wx * 8192 + 4096, &P.mQ8, bars + BB_Q, b * 8, wx * 64 + 32, 0);
        }
        if (i < 0) continue;
        conv_sum(ch < GCH ? sm + B_Y + (ch & 7) * 4224 : P.yt + (ch - GCH) * 4096, ch < GCH ? 132 : 128, red, red + 2 * B_PLANE, tl, bars + BB_FREE + (wg * 2 + buf) * 8);
        if (ch >= GCH) {
            __syncwarp();
            if (lane == 0) mbar_arrive(bars + BB_ROWS + wg * 8);
            if (wx == wg) {
                mbar_wait(bars + BB_ROWS + wg * 8, 0);
                if (lane == 0) red_release(&P.cnt[(CNT_Y + ((ch - GCH) >> 5)) * 32], 4);
                __syncwarp();
            }
        }
        if (i == nch - 1) {
            bar_sync(5, 128);
            mbar_wait(bars + BB_Q, 0);
#pragma unroll 1
            for (int sl = 2 * wx; sl < 2 * wx + 2; sl++) {
                const int ck = sl * 32 + lane;
                const unsigned char* yp = sm + B_Y + (ck & 1) * 2112 + (ck >> 1) * 16;
                const uint4* qp = (const uint4*)(sm + B_Q + sl * 4096) + lane;
                const int oo = (sl & 1) ? (3 * B_UH + 255) / 256 * 256 + (wx & 1) * 8192 + (wx >> 1) * B_WG : B_O + wx * 8192;
                unsigned char* op = sm + oo + lane * 32;
                const int sw = (lane & 4) << 2;
                uint4 yy[8];
#pragma unroll
                for (int z = 0; z < 8; z++) yy[z] = *(const uint4*)(yp + z * 4224);
#pragma unroll
                for (int t = 0; t < 8; t++) {
                    const uint4 qv = qp[t * 32];
                    const uint32_t sel = (t & 1) ? 0x7632 : 0x5410;
                    uint32_t o[4];
#pragma unroll
                    for (int z = 0; z < 4; z++) o[z] = bmul(__byte_perm(((const uint32_t*)&yy[2 * z])[t >> 1], ((const uint32_t*)&yy[2 * z + 1])[t >> 1], sel), ((const uint32_t*)&qv)[z]);
                    *(float4*)(op + t * 1024 + sw) = make_float4(bf_lo(o[0]), bf_hi(o[0]), bf_lo(o[1]), bf_hi(o[1]));
                    *(float4*)(op + t * 1024 + (sw ^ 16)) = make_float4(bf_lo(o[2]), bf_hi(o[2]), bf_lo(o[3]), bf_hi(o[3]));
                }
                fence_async_smem();
                __syncwarp();
                if (lane == 0) { tma_st3(&P.mO8, sb + oo, DM + b * 8, sl * 32, 0); bulk_commit(); }
            }
        }
    }
    if (lane == 0) bulk_wait0_read();
    __syncwarp();
}

__global__ void __cluster_dims__(2, 1, 1) __launch_bounds__(NTHREADS, 1) fused_kernel(const __grid_constant__ Params P) {
    extern __shared__ __align__(1024) unsigned char sm[];
    const unsigned t_start = clock();
    const uint32_t sb = smem_u32(sm), bars = sb + SM_MISC;
    const int tid = threadIdx.x, warp = __shfl_sync(~0u, tid >> 5, 0), lane = tid & 31;
    const int wg = warp >> 2, wx = warp & 3, b = blockIdx.x;
    const bool is_a = b >= NB_CTA;
    if (is_a) {
        if (tid == 288) { prefetch_tmap(&P.mX); prefetch_tmap(&P.mB); }
        if (tid == 256 || tid == 0 || tid == 128) {
            if (sb & 1023) __trap();
#pragma unroll
            for (int s = 0; s < 37; s++)
                if ((s < 8 ? 256 : s < 22 ? 128 : 0) == tid)
                    mbar_init(bars + s * 8, (s >= 4 && s < 8) || (s >= 15 && s < 22) ? 16 : (s >= 22 && s < 26) ? 4 : s == 36 ? 8 : s == 26 || s == 29 || s == 30 ? 2 : 1);
            asm volatile("fence.mbarrier_init.release.cluster;" ::: "memory");
        }
        __syncwarp();
        asm volatile("barrier.cluster.arrive.relaxed.aligned;" ::: "memory");
        if (tid == 256) {
            const int pg = ((b - NB_CTA) >> 1) % 5 + 5 * (b & 1);
            mbar_expect_tx(bars + BAR_FULL1, STAGE_BYTES);
            tma_ld4(sb, &P.mB, bars + BAR_FULL1, 0, 0, 0, 8 * pg);
            {
                tma_ld5(sb + A_PART, &P.mX, bars + BAR_FULL1, 0, 0, 0, 0, ((b - NB_CTA) >> 1) / 5);
                tma_ld5(sb + A_PART + 16384, &P.mX, bars + BAR_FULL1, 0, 0, 0, 16, ((b - NB_CTA) >> 1) / 5);
            }
        }
        __syncwarp();
        asm volatile("barrier.cluster.wait.aligned;" ::: "memory");
        if (warp == 8) {
            const int cl = (b - NB_CTA) >> 1, r = b & 1;
#pragma unroll
            for (int it = 0; it < 4; it++) {
                const uint32_t st = sb + it * STAGE_BYTES, fb = bars + BAR_FULL1 + it * 8;
                if (it) e_tma_ld5_mc(st + A_PART + r * 16384, &P.mX, fb, it * 64, 16 * r, cl / 5);
                if (it < 3) {
                    e_expect_tx(fb + 8, STAGE_BYTES);
                    e_tma_ld4(st + STAGE_BYTES, &P.mB, fb + 8, it * 64 + 64, 8 * (cl % 5 + 5 * r));
                }
            }
        }
    } else {
        if (tid == 288) { prefetch_tmap(&P.mK8); prefetch_tmap(&P.mV8); prefetch_tmap(&P.mK3); }
        if (tid == 256) {
#pragma unroll
            for (int s = 0; s < 33; s++) mbar_init(bars + s * 8, s < 13 ? 4 : 1);
        }
        __syncthreads();
    }

    if (wg == 2) {
        asm volatile("setmaxnreg.dec.sync.aligned.u32 88;");
        if (is_a) {
            if (warp > 8) {
                mbar_wait(bars + BAR_FULL1, 0);
                if (warp < 11) a_poles(P, sm, sb, warp - 9, lane);
                else if (lane == 0) { prefetch_tmap(&P.mC); prefetch_tmap(&P.mO); }
                __syncwarp();
            }
        } else {
            if (wx == 1 && lane == 0) { prefetch_tmap(&P.mQ8); prefetch_tmap(&P.mO8); }
            if (wx == 3) {
                take_epoch(P, sm, lane);
                if (lane < 10) *(__nv_bfloat16*)(sm + SM_POLE + lane * 2) = P.ssm_d[b_channel(b, lane & 1, lane >> 1)];
            }
            __syncwarp();
            if (wx == 3 && lane == 0) mbar_arrive(bars + BB_EPOCH);
            delay_until(t_start, P0_DELAY + warp * P_STEP);
#pragma unroll 1
            for (int i = 0, blk = warp * 52 + b; blk < 640; i++, blk += 208)
                b_prep_block(P, blk, lane, sb + B_PBUF + wx * P_BUF, bars + BB_PREP + warp * 8, i, sm);
        }
        if (is_a) {
            a_aux(P, sm, sb, warp, lane);
            if (warp == 9) b_final(P, b - NB_CTA, lane, smem_epoch(sm));
        } else {
            b_aux(P, sm, sb, warp, lane);
        }
    } else {
        asm volatile("setmaxnreg.inc.sync.aligned.u32 208;");
        int n;
        uint32_t uh, red, p23d, fullb, xm[32];
#pragma unroll
        for (int z = 0; z < 32; z++) xm[z] = 0;
        if (is_a) {
            a_first(P, xm, sm, sb, warp, lane);
            n = 1;
            uh = sb + HOST_UH(wg); red = uh + HOST_P01; p23d = HOST_P23 - HOST_P01; fullb = bars + (wg ? BAR_HOSTF1 : BAR_HOSTF);
            {
                const int tl = 32 * wx + lane;
                mbar_wait(bars + BAR_EMPTY1 + 8, 0);
                if (tl < 15) *(uint4*)(sm + HOST_UH(wg) + 4096 + tl * 16) = make_uint4(0, 0, 0, 0);
                else if (tl < 19) *(uint4*)(sm + HOST_UH(wg) + ((tl & 2) ? HOST_P23 : HOST_P01) + (tl & 1) * B_PLANE) = make_uint4(0, 0, 0, 0);
                fence_async_smem();
            }
        } else {
            if (wg == 1) bar_arrive(1, 256);
            delay_until(t_start, P0_DELAY + warp * P_STEP);
            b_prep_block(P, warp * 52 + b, lane, sb + wg * B_WG + B_UH + wx * P_BUF, bars + BB_PREP + warp * 8, 0, sm);
            mbar_wait(bars + BB_EPOCH, 0);
            if (wx == 0) b_load(P, sb, b, wg, 0, smem_epoch(sm));
            bar_sync(3 + wg, 128);
            if (wx < 2 && lane == 0) mbar_arrive(bars + BB_GATE);
            {
                const int i = tid & 127;
                unsigned char* base = sm + wg * B_WG;
                if (i < 45) *(uint4*)(base + (i / 15) * B_UH + 4096 + (i % 15) * 16) = make_uint4(0, 0, 0, 0);
                if (i >= 48 && i < 56) *(uint4*)(base + 3 * B_UH + ((i >> 2) & 1) * B_RED + (i & 3) * B_PLANE) = make_uint4(0, 0, 0, 0);
                fence_async_smem();
                bar_sync(3 + wg, 128);
            }
            n = (wg == 0 || b < 12) ? 5 : 4;
            uh = sb + wg * B_WG; red = uh + 3 * B_UH; p23d = 2 * B_PLANE; fullb = bars + BB_FULL + wg * 24;
        }
        float d[128];
#pragma unroll 1
        for (int m = 0; m < n; m++) {
            const int buf = m & 1, ub = m >= 3 ? m - 3 : m;
            mbar_wait(fullb + ub * 8, m >= 3);
            if (wx == 0 && lane == 0) patch_tap0(sm + (uh - sb) + ub * B_UH + 4224, *(const __nv_bfloat16*)(sm + (is_a ? SM_POLE + 2052 + 2 * wg : SM_POLE + (2 * m + wg) * 2)));
            __syncwarp();
            bar_sync(is_a ? 2 + wg : 1 + wg, is_a ? 128 : 256);
            WG_FENCE();
            conv_mma<0>(d, make_desc(uh + ub * B_UH + 4224, 128, 16, 0), make_desc(uh + ub * B_UH, 128, 128, 0), P.zero);
            WG_WAIT(CONV_TAIL);
            if (!is_a && (m < 4 || (wg == 0 && b < 12))) bar_arrive(2 - wg, 256);
            if (m >= 2) mbar_wait(bars + BB_FREE + (wg * 2 + buf) * 8, ((m >> 1) - 1) & 1);
            WG_WAIT(0);
            conv_fold(d, red + buf * B_RED, red + buf * B_RED + p23d, wx, lane);
            __syncwarp();
            if (!is_a && lane == 0) mbar_arrive(bars + BB_RDY + (wg * 2 + buf) * 8);
        }
        if (is_a) {
            bar_sync(2 + wg, 128);
            conv_sum(P.yt + (2 * (b - NB_CTA) + wg) * 4096, 128, red, red + p23d, 32 * wx + lane, 0);
            __syncwarp();
            if (lane == 0) mbar_arrive(bars + BAR_HOSTD);
            a_second(P, xm, sm, sb, warp, lane);
        } else if (FA + ((wg ^ 1) * 4 + wx) * 52 + (51 - b) < 224) {
            b_final(P, FA + ((wg ^ 1) * 4 + wx) * 52 + (51 - b), lane, smem_epoch(sm));
        }
    }
}

__device__ float2 g_fb[SEQ * DM];
__global__ void fb_gemm1(const __nv_bfloat16* x, const __nv_bfloat16* bre, const __nv_bfloat16* bim) {
    const int t = blockIdx.x, p = threadIdx.x;
    float a = 0.f, b = 0.f;
    for (int k = 0; k < DM; k++) { const float xv = __bfloat162float(x[t * DM + k]); a = fmaf(xv, __bfloat162float(bre[p * DM + k]), a); b = fmaf(xv, __bfloat162float(bim[p * DM + k]), b); }
    g_fb[t * DM + p] = make_float2(a, b);
}
__global__ void fb_scan(const Params P) {
    const int p = blockIdx.x * 32 + threadIdx.x;
    const float lx = __bfloat162float(P.lam_re[p]), ly = __bfloat162float(P.lam_im[p]);
    const float2 L = lam_bar(__bfloat162float(P.log_dt[p]), lx, ly);
    const float nr = L.x - 1.f, ni = L.y, den = lx * lx + ly * ly;
    const float2 cf = make_float2(2.f * (nr * lx + ni * ly) / den, 2.f * (ni * lx - nr * ly) / den);
    float2 h = make_float2(0.f, 0.f);
    for (int t = 0; t < SEQ; t++) { h = cfma(L, h, g_fb[t * DM + p]); g_fb[t * DM + p] = cmul(cf, h); }
}
__global__ void fb_gemm2(const Params P, const __nv_bfloat16* x) {
    const int t = blockIdx.x, dd = threadIdx.x;
    float a = bf16r(__bfloat162float(x[t * DM + dd]) * __bfloat162float(P.dskip[dd]));
    for (int p = 0; p < DM; p++) { const float2 h = g_fb[t * DM + p]; a += h.x * __bfloat162float(P.c_re[dd * DM + p]) - h.y * __bfloat162float(P.c_im[dd * DM + p]); }
    P.out[t * 1280 + dd] = a;
}
__global__ void fb_conv(const Params P) {
    __shared__ float u[SEQ], hh[SEQ];
    const int ch = blockIdx.x;
    for (int s = threadIdx.x; s < SEQ; s += blockDim.x) {
        float a = 0.f;
        for (int jj = 3; jj >= 0; jj--) a = bf16r(a + bf16r((s >= jj ? __bfloat162float(P.k[(s - jj) * DM + ch]) : 0.f) * __bfloat162float(P.shift_k[ch * 4 + jj])));
        u[s] = bf16r(a * __bfloat162float(P.v[s * DM + ch]));
        hh[s] = __bfloat162float(P.ssm_k[ch * SEQ + s]);
    }
    __syncthreads();
    for (int s = threadIdx.x; s < SEQ; s += blockDim.x) {
        float a = 0.f;
        for (int jj = 0; jj <= s; jj++) a = fmaf(hh[jj], u[s - jj], a);
        P.out[s * 1280 + DM + ch] = bf16r(__bfloat162float(P.q[s * DM + ch]) * bf16r(bf16r(a) + bf16r(u[s] * __bfloat162float(P.ssm_d[ch]))));
    }
}

typedef CUresult (*EncFn)(CUtensorMap*, CUtensorMapDataType, cuuint32_t, void*, const cuuint64_t*, const cuuint64_t*, const cuuint32_t*, const cuuint32_t*,
                          CUtensorMapInterleave, CUtensorMapSwizzle, CUtensorMapL2promotion, CUtensorMapFloatOOBfill);

}

extern "C" void kernel_launch(void* const* d_in, const int* in_sizes, int n_in, void* d_out, int out_size) {
    static EncFn enc = nullptr;
    static void* sym[8];
    static int clusters = 0;
    if (!enc) {
        void* fn = nullptr; cudaDriverEntryPointQueryResult qr;
        cudaGetDriverEntryPoint("cuTensorMapEncodeTiled", &fn, cudaEnableDefault, &qr);
        enc = (EncFn)fn;
        cudaGetSymbolAddress(&sym[0], g_h); cudaGetSymbolAddress(&sym[2], g_agg);
        cudaGetSymbolAddress(&sym[3], g_flag_h); cudaGetSymbolAddress(&sym[4], g_cnt); cudaGetSymbolAddress(&sym[6], g_ut); cudaGetSymbolAddress(&sym[7], g_yt); cudaGetSymbolAddress(&sym[5], g_epoch);
        cudaFuncSetAttribute(fused_kernel, cudaFuncAttributeMaxDynamicSharedMemorySize, SMEM_BYTES);
        cudaLaunchConfig_t cfg = {};
        cfg.gridDim = dim3(NCTA); cfg.blockDim = dim3(NTHREADS); cfg.dynamicSmemBytes = SMEM_BYTES;
        cudaLaunchAttribute at;
        at.id = cudaLaunchAttributeClusterDimension; at.val.clusterDim.x = 2; at.val.clusterDim.y = 1; at.val.clusterDim.z = 1;
        cfg.attrs = &at; cfg.numAttrs = 1;
        if (cudaOccupancyMaxActiveClusters(&clusters, fused_kernel, &cfg) != cudaSuccess) { clusters = 0; (void)cudaGetLastError(); }
    }
    Params P;
    const cuuint32_t ones[5] = {1, 1, 1, 1, 1};
    const CUtensorMapInterleave IL = CU_TENSOR_MAP_INTERLEAVE_NONE;
    const CUtensorMapSwizzle SW = CU_TENSOR_MAP_SWIZZLE_128B;
    const CUtensorMapL2promotion PR = CU_TENSOR_MAP_L2_PROMOTION_L2_128B;
    const CUtensorMapFloatOOBfill OB = CU_TENSOR_MAP_FLOAT_OOB_FILL_NONE;
    int rc = 0;
    {
        cuuint64_t gd[5] = {640, 2, 4, 32, 8}, gs[4] = {1280, 64 * 1280, 2 * 1280, 256 * 1280};
        cuuint32_t bx[5] = {64, 2, 4, 16, 1};
        rc |= (int)enc(&P.mX, CU_TENSOR_MAP_DATA_TYPE_BFLOAT16, 5, d_in[0], gd, gs, bx, ones, IL, SW, PR, OB);
    }
    {
        char *a = (char*)d_in[3], *b = (char*)d_in[4];
        P.swap = b < a;
        cuuint64_t gd[4] = {640, 8, 2, 80}, gs[3] = {1280, (cuuint64_t)(P.swap ? a - b : b - a), 8 * 1280};
        cuuint32_t bx[4] = {64, 8, 2, 8};
        rc |= (int)enc(&P.mB, CU_TENSOR_MAP_DATA_TYPE_BFLOAT16, 4, P.swap ? b : a, gd, gs, bx, ones, IL, SW, PR, OB);
    }
    {
        cuuint64_t gd[5] = {1280, 2, 4, 32, 8}, gs[4] = {5120, 64 * 5120, 2 * 5120, 256 * 5120};
        cuuint32_t bx[5] = {32, 2, 4, 16, 1};
        rc |= (int)enc(&P.mO, CU_TENSOR_MAP_DATA_TYPE_FLOAT32, 5, d_out, gd, gs, bx, ones, IL, SW, PR, OB);
    }
    {
        char *a = (char*)d_in[5], *b = (char*)d_in[6];
        P.swap_c = b < a;
        cuuint64_t gd[3] = {640, 640, 2}, gs[2] = {1280, (cuuint64_t)(P.swap_c ? a - b : b - a)};
        cuuint32_t bx[3] = {32, 64, 2};
        rc |= (int)enc(&P.mC, CU_TENSOR_MAP_DATA_TYPE_BFLOAT16, 3, P.swap_c ? b : a, gd, gs, bx, ones, IL, CU_TENSOR_MAP_SWIZZLE_64B, PR, OB);
    }
    {
        cuuint64_t gd[3] = {640, 256, 8}, gs[2] = {8 * 1280, 1280};
        cuuint32_t bx8[3] = {32, 8, 8}, bx3[3] = {32, 8, 3};
        const CUtensorMapSwizzle NS = CU_TENSOR_MAP_SWIZZLE_NONE;
        const CUtensorMapL2promotion P128 = CU_TENSOR_MAP_L2_PROMOTION_L2_128B;
        rc |= (int)enc(&P.mK8, CU_TENSOR_MAP_DATA_TYPE_BFLOAT16, 3, d_in[10], gd, gs, bx8, ones, IL, NS, P128, OB);
        rc |= (int)enc(&P.mK3, CU_TENSOR_MAP_DATA_TYPE_BFLOAT16, 3, d_in[10], gd, gs, bx3, ones, IL, NS, P128, OB);
        rc |= (int)enc(&P.mV8, CU_TENSOR_MAP_DATA_TYPE_BFLOAT16, 3, d_in[11], gd, gs, bx8, ones, IL, NS, P128, OB);
        cuuint32_t bxn[3] = {8, 32, 8};
        rc |= (int)enc(&P.mQ8, CU_TENSOR_MAP_DATA_TYPE_BFLOAT16, 3, d_in[9], gd, gs, bxn, ones, IL, NS, CU_TENSOR_MAP_L2_PROMOTION_NONE, OB);
        cuuint64_t go[3] = {1280, 256, 8}, gso[2] = {8 * 5120, 5120};
        rc |= (int)enc(&P.mO8, CU_TENSOR_MAP_DATA_TYPE_FLOAT32, 3, d_out, go, gso, bxn, ones, IL, CU_TENSOR_MAP_SWIZZLE_32B, P128, OB);
    }
    P.lam_re = (const __nv_bfloat16*)d_in[1]; P.lam_im = (const __nv_bfloat16*)d_in[2];
    P.c_re = (const __nv_bfloat16*)d_in[5]; P.c_im = (const __nv_bfloat16*)d_in[6];
    P.log_dt = (const __nv_bfloat16*)d_in[7]; P.dskip = (const __nv_bfloat16*)d_in[8];
    P.q = (const __nv_bfloat16*)d_in[9]; P.k = (const __nv_bfloat16*)d_in[10]; P.v = (const __nv_bfloat16*)d_in[11];
    P.shift_k = (const __nv_bfloat16*)d_in[12]; P.ssm_k = (const __nv_bfloat16*)d_in[13]; P.ssm_d = (const __nv_bfloat16*)d_in[14];
    P.out = (float*)d_out;
    P.zero = 0;
    P.h = (unsigned char*)sym[0]; P.agg = (unsigned long long*)sym[2];
    P.flag_h = (unsigned*)sym[3]; P.cnt = (unsigned*)sym[4]; P.ut = (unsigned char*)sym[6]; P.yt = (unsigned char*)sym[7]; P.epoch = (unsigned*)sym[5];
    if (rc == 0 && clusters >= NCTA / 2) {
        fused_kernel<<<NCTA, NTHREADS, SMEM_BYTES>>>(P);
    } else {
        fb_gemm1<<<SEQ, DM>>>((const __nv_bfloat16*)d_in[0], (const __nv_bfloat16*)d_in[3], (const __nv_bfloat16*)d_in[4]);
        fb_scan<<<DM / 32, 32>>>(P);
        fb_gemm2<<<SEQ, DM>>>(P, (const __nv_bfloat16*)d_in[0]);
        fb_conv<<<DM, 256>>>(P);
    }
}
```
